```python
import torch

def _softmax(x, axis=-1):
    return torch.softmax(x, dim=axis)

def _gelu(x):
    return torch.nn.functional.gelu(x, approximate='tanh')

def _silu(x):
    return torch.nn.functional.silu(x)

def _sigmoid(x):
    return torch.sigmoid(x)

def _layernorm(x, axis=-1, eps=1e-05):
    m = x.mean(dim=axis, keepdim=True)
    v = x.var(dim=axis, keepdim=True, unbiased=False)
    return (x - m) / torch.sqrt(v + eps)

def _scatter_add(tgt, idx, src, axis=0):
    return tgt.clone().index_add_(axis, idx, src)

def _segment_sum(src, seg, n):
    out = torch.zeros((n,) + src.shape[1:], dtype=src.dtype)
    return out.index_add_(0, seg, src)

def _pad(x, pw):
    flat = tuple((v for pair in reversed(pw) for v in pair))
    return torch.nn.functional.pad(x, flat)
kernel_name = 'adaLN_cond__gqa_block_cached__geglu_ffn__decode'

def setup_inputs():

    _w = lambda a: (lambda t: t.to(torch.bfloat16) if t.is_floating_point() else t)(torch.as_tensor(a))

    def _A_setup():
        B, Sq, D = (2, 1, 512)
        Hq, Hkv, Sk, Dh = (32, 8, 32768, 128)
        assert Hq % Hkv == 0, (Hq, Hkv)
        return {'x': _w((lambda *s: torch.randn(*s, dtype=torch.bfloat16) * 0.1)(B, Sq, D)), 'k_cache': _w((lambda *s: torch.randn(*s, dtype=torch.bfloat16) * 0.8)(B, Hkv, Sk, Dh)), 'v_cache': _w((lambda *s: torch.randn(*s, dtype=torch.bfloat16) * 0.8)(B, Hkv, Sk, Dh)), 'wq': _w((lambda *s: torch.randn(*s, dtype=torch.bfloat16) * 0.8)(D, Hq * Dh) * D ** (-0.5)), 'wo': _w((lambda *s: torch.randn(*s, dtype=torch.bfloat16) * 0.8)(Hq * Dh, D) * (Hq * Dh) ** (-0.5))}
    _A_in = _A_setup()

    def _B_setup():
        B, S, D, F = (2, 1, 512, 1792)
        return {'x': _w((lambda *s: torch.randn(*s, dtype=torch.bfloat16) * 0.1)(B, S, D)), 'w_gate': _w((lambda *s: torch.randn(*s, dtype=torch.bfloat16) * 0.1)(D, F)), 'w_up': _w((lambda *s: torch.randn(*s, dtype=torch.bfloat16) * 0.1)(D, F)), 'w_down': _w((lambda *s: torch.randn(*s, dtype=torch.bfloat16) * 0.1)(F, D))}
    _B_in = _B_setup()
    return {'A_x': _A_in['x'], 'A_k_cache': _A_in['k_cache'], 'A_v_cache': _A_in['v_cache'], 'A_wq': _A_in['wq'], 'A_wo': _A_in['wo'], 'B_x': _B_in['x'], 'B_w_gate': _B_in['w_gate'], 'B_w_up': _B_in['w_up'], 'B_w_down': _B_in['w_down'], 'c': _w((lambda *s: torch.randn(*s, dtype=torch.bfloat16) * 0.4)(2, 512) * 8.0), 'w_mod': _w((lambda *s: torch.randn(*s, dtype=torch.bfloat16) * 0.4)(512, 6 * 512) * 512 ** (-0.5) * 8.0)}

def reference(A_x, A_k_cache, A_v_cache, A_wq, A_wo, B_x, B_w_gate, B_w_up, B_w_down, c, w_mod):

    def _A_ref(x, k_cache, v_cache, wq, wo):
        B, Sq, D = x.shape
        Hq, Dh = (32, 128)
        Hkv = k_cache.shape[1]
        rep = Hq // Hkv
        q = (lambda x, *d: x.permute(*d))((x @ wq).reshape(B, Sq, Hq, Dh), 0, 2, 1, 3)
        k = (lambda x, n, axis: torch.repeat_interleave(x, n, dim=axis))(k_cache, rep, axis=1)
        v = (lambda x, n, axis: torch.repeat_interleave(x, n, dim=axis))(v_cache, rep, axis=1)
        scores = torch.einsum('bhqd,bhkd->bhqk', q, k) * Dh ** (-0.5)
        p = _softmax(scores, axis=-1)
        o = torch.einsum('bhqk,bhkd->bhqd', p, v)
        return (lambda x, *d: x.permute(*d))(o, 0, 2, 1, 3).reshape(B, Sq, Hq * Dh) @ wo

    def _B_ref(x, w_gate, w_up, w_down):
        return _gelu(x @ w_gate) * (x @ w_up) @ w_down
    x = A_x
    mod = (_silu(c) @ w_mod).reshape(c.shape[0], 6, 1, -1)
    sa, ca, ga, sb, cb, gb = (mod[:, 0].clone(), mod[:, 1].clone(), mod[:, 2].clone(), mod[:, 3].clone(), mod[:, 4].clone(), mod[:, 5].clone())
    h = _layernorm(x, axis=-1) * (1 + ca) + sa
    x = x + ga * _A_ref(h, A_k_cache, A_v_cache, A_wq, A_wo)
    h = _layernorm(x, axis=-1) * (1 + cb) + sb
    x = x + gb * _B_ref(h, B_w_gate, B_w_up, B_w_down)
    return x
```

```cpp
#include <cuda_runtime.h>
#include <cuda_bf16.h>
#include <cuda.h>
#include <stdint.h>

namespace {

constexpr int D      = 512;
constexpr int HQ     = 32;
constexpr int HKV    = 8;
constexpr int SK     = 32768;
constexpr int DH     = 128;
constexpr int FF     = 1792;
constexpr int NCTA   = 128;
constexpr int NCONS  = 256;
constexpr int NTHR   = 288;
constexpr int TILE_KEYS  = 128;
constexpr int TILE_BYTES = TILE_KEYS * DH * 2;
constexpr int NST    = 6;
constexpr int NTILES = (SK / 8) / TILE_KEYS;
constexpr int NIDX   = 2 * NTILES;
constexpr int MAXFLY = 2;
constexpr int NFFN   = 56;
constexpr int FC     = 32;
constexpr int RED0   = 64;
constexpr int NREP   = 8;
#define WO_AT 61

constexpr int H1_HS = 136;
struct __align__(128) Mail {
    float  h1[HKV * 16 * 4 * H1_HS];
    float4 rs1[64 * 32 * 4];
    float4 rs3[64 * NFFN * 4];
    uint2  ag[NREP * 64 * 4];
};
static_assert(sizeof(Mail) == NCTA * 5120, "mail size");
__device__ Mail     g_mail;
__device__ uint2    g_mod[6 * D];
__device__ uint2    g_q[HQ * DH];
__device__ unsigned g_epoch;
#define TS(i)
#define TSW(i)

constexpr int SM_RING   = 0;
constexpr int SM_SCR    = NST * TILE_BYTES;
constexpr int SM_ML     = SM_SCR + 18432;
constexpr int SM_SMALL  = SM_ML + 256;
constexpr int SM_BAR    = SM_SMALL + 4096;
constexpr int SM_TOTAL  = SM_BAR + 128;
constexpr int SM_ALLOC  = SM_TOTAL + 1024;

constexpr unsigned SPIN_LIMIT = 1u << 24;

__device__ __forceinline__ uint32_t smem_u32(const void* p) { return (uint32_t)__cvta_generic_to_shared(p); }
__device__ __forceinline__ void mbar_init(uint32_t bar, uint32_t cnt) {
    asm volatile("mbarrier.init.shared::cta.b64 [%0], %1;" :: "r"(bar), "r"(cnt) : "memory");
}
__device__ __forceinline__ void mbar_expect_tx(uint32_t bar, uint32_t bytes) {
    asm volatile("mbarrier.arrive.expect_tx.shared::cta.b64 _, [%0], %1;" :: "r"(bar), "r"(bytes) : "memory");
}
__device__ __forceinline__ void mbar_arrive(uint32_t bar) {
    asm volatile("mbarrier.arrive.shared::cta.b64 _, [%0];" :: "r"(bar) : "memory");
}
__device__ __forceinline__ void mbar_wait(uint32_t bar, uint32_t parity) {
    uint32_t ok;
    unsigned spins = 0;
    do {
        asm volatile("{\n.reg .pred p;\nmbarrier.try_wait.parity.shared::cta.b64 p, [%1], %2;\nselp.u32 %0, 1, 0, p;\n}"
                     : "=r"(ok) : "r"(bar), "r"(parity) : "memory");
        if (++spins > SPIN_LIMIT) __trap();
    } while (!ok);
}
__device__ __forceinline__ void tma2d(uint32_t dst, const CUtensorMap* m, int c0, int c1, uint32_t bar, uint64_t pol) {
    asm volatile("cp.async.bulk.tensor.2d.shared::cluster.global.mbarrier::complete_tx::bytes.L2::cache_hint"
                 " [%0], [%1, {%3, %4}], [%2], %5;"
                 :: "r"(dst), "l"(m), "r"(bar), "r"(c0), "r"(c1), "l"(pol) : "memory");
}
__device__ __forceinline__ void ldsm4(uint32_t (&r)[4], uint32_t addr) {
    asm volatile("ldmatrix.sync.aligned.m8n8.x4.shared.b16 {%0,%1,%2,%3}, [%4];"
                 : "=r"(r[0]), "=r"(r[1]), "=r"(r[2]), "=r"(r[3]) : "r"(addr) : "memory");
}
__device__ __forceinline__ void ldsm4t(uint32_t (&r)[4], uint32_t addr) {
    asm volatile("ldmatrix.sync.aligned.m8n8.x4.trans.shared.b16 {%0,%1,%2,%3}, [%4];"
                 : "=r"(r[0]), "=r"(r[1]), "=r"(r[2]), "=r"(r[3]) : "r"(addr) : "memory");
}
__device__ __forceinline__ void mma16816(float (&c)[4], const uint32_t (&a)[4], uint32_t b0, uint32_t b1) {
    asm volatile("mma.sync.aligned.m16n8k16.row.col.f32.bf16.bf16.f32 {%0,%1,%2,%3}, {%4,%5,%6,%7}, {%8,%9}, {%0,%1,%2,%3};"
                 : "+f"(c[0]), "+f"(c[1]), "+f"(c[2]), "+f"(c[3])
                 : "r"(a[0]), "r"(a[1]), "r"(a[2]), "r"(a[3]), "r"(b0), "r"(b1));
}
__device__ __forceinline__ uint32_t movtrans(uint32_t a) {
    uint32_t d;
    asm volatile("movmatrix.sync.aligned.m8n8.trans.b16 %0, %1;" : "=r"(d) : "r"(a));
    return d;
}
__device__ __forceinline__ void cons_bar() { asm volatile("bar.sync 1, 256;" ::: "memory"); }
__device__ __forceinline__ float ex2(float x) { float y; asm("ex2.approx.ftz.f32 %0, %1;" : "=f"(y) : "f"(x)); return y; }
__device__ __forceinline__ uint32_t pack_bf16(float lo, float hi) {
    uint32_t r; asm("cvt.rn.bf16x2.f32 %0, %1, %2;" : "=r"(r) : "f"(hi), "f"(lo)); return r;
}
__device__ __forceinline__ float bf_lo(uint32_t w) { return __uint_as_float(w << 16); }
__device__ __forceinline__ float bf_hi(uint32_t w) { return __uint_as_float(w & 0xffff0000u); }
__device__ __forceinline__ float bfr(float x) { return bf_lo(pack_bf16(x, 0.f)); }
__device__ __forceinline__ float bfld(const __nv_bfloat16* p) { return __bfloat162float(*p); }

__device__ __forceinline__ uint4 ldg_stream(const void* p) {
    uint4 v;
    asm volatile("ld.global.nc.L1::no_allocate.L2::128B.v4.u32 {%0,%1,%2,%3}, [%4];"
                 : "=r"(v.x), "=r"(v.y), "=r"(v.z), "=r"(v.w) : "l"(p));
    return v;
}
__device__ __forceinline__ uint4 ld_mail16(const void* p) {
    uint4 v;
    asm volatile("ld.relaxed.gpu.global.v4.u32 {%0,%1,%2,%3}, [%4];"
                 : "=r"(v.x), "=r"(v.y), "=r"(v.z), "=r"(v.w) : "l"(p) : "memory");
    return v;
}
__device__ __forceinline__ uint2 ld_mail8(const void* p) {
    uint2 v;
    asm volatile("ld.relaxed.gpu.global.v2.u32 {%0,%1}, [%2];" : "=r"(v.x), "=r"(v.y) : "l"(p) : "memory");
    return v;
}
__device__ __forceinline__ void st_mail16(void* p, uint4 v) {
    asm volatile("st.relaxed.gpu.global.v4.u32 [%0], {%1,%2,%3,%4};" :: "l"(p), "r"(v.x), "r"(v.y), "r"(v.z), "r"(v.w) : "memory");
}
__device__ __forceinline__ void st_mail8(void* p, uint2 v) {
    asm volatile("st.relaxed.gpu.global.v2.u32 [%0], {%1,%2};" :: "l"(p), "r"(v.x), "r"(v.y) : "memory");
}
__device__ __forceinline__ uint32_t nz(float x) { uint32_t u = __float_as_uint(x); return u ? u : 0x80000000u; }
__device__ __forceinline__ bool full4(const uint4& v) { return v.x && v.y && v.z && v.w; }
__device__ __forceinline__ void spin_guard(unsigned& s) { if (++s > SPIN_LIMIT) __trap(); }

template <int N, int MASK> struct Halve {
    static __device__ __forceinline__ void run(float* v, int lane) {
        const bool up = lane & MASK;
#pragma unroll
        for (int i = 0; i < N / 2; i++) {
            float keep = up ? v[i + N / 2] : v[i];
            float send = up ? v[i] : v[i + N / 2];
            v[i] = keep + __shfl_xor_sync(0xffffffffu, send, MASK);
        }
    }
};

struct Params {
    const __nv_bfloat16 *x, *c, *w_mod, *wq;
    __nv_bfloat16* out;
};

constexpr float LOG2E = 1.4426950408889634f;
constexpr float SCALE = 0.08838834764831845f;

__global__ void __launch_bounds__(NTHR, 1)
fused_kernel(const Params p,
             const __grid_constant__ CUtensorMap tm_k, const __grid_constant__ CUtensorMap tm_v,
             const __grid_constant__ CUtensorMap tm_wo, const __grid_constant__ CUtensorMap tm_wg,
             const __grid_constant__ CUtensorMap tm_wu, const __grid_constant__ CUtensorMap tm_wd)
{
    extern __shared__ uint8_t smem_raw[];
    const uint32_t sbase = (smem_u32(smem_raw) + 1023u) & ~1023u;
    uint8_t* smem = smem_raw + (sbase - smem_u32(smem_raw));
    const int tid = threadIdx.x, lane = tid & 31, warp = tid >> 5;
    const int cta = blockIdx.x;
    const int bat = cta >> 6, hkv = (cta >> 3) & 7, split = cta & 7;
    const int j16 = bat * 8 + split;
    const bool is_ffn = cta < NFFN, is_red = cta >= RED0;
    const uint32_t bar_full = sbase + SM_BAR, bar_empty = sbase + SM_BAR + 8 * NST;

    if (warp == 8) {
        if (lane == 0) {
            for (int i = 0; i < NST; i++) { mbar_init(bar_full + 8 * i, 1); mbar_init(bar_empty + 8 * i, 8); }
            asm volatile("fence.mbarrier_init.release.cluster;" ::: "memory");
            asm volatile("fence.proxy.async.shared::cta;" ::: "memory");
        }
        __syncwarp();
        asm volatile("bar.arrive 2, 288;" ::: "memory");
        if (lane == 0) {
            uint64_t pol;
            asm volatile("createpolicy.fractional.L2::evict_first.b64 %0, 1.0;" : "=l"(pol));
            const int row0 = ((bat * HKV + hkv) * SK + split * TILE_KEYS) * 2;
            auto issue_w = [&](int idx) {
                const int st = idx % NST;
                const uint32_t dst = sbase + SM_RING + st * TILE_BYTES, bar = bar_full + 8 * st;
                mbar_wait(bar_empty + 8 * st, ((idx / NST) & 1) ^ 1);
                mbar_expect_tx(bar, TILE_BYTES);
                if (idx == 64) {
                    const int h = hkv * 4 + (j16 >> 2), cq = j16 & 3;
                    tma2d(dst, &tm_wo, cq * 128, h * 128, bar, pol);
                    tma2d(dst + 16384, &tm_wo, cq * 128 + 64, h * 128, bar, pol);
                } else if (idx == 65 || idx == 66) {
                    const CUtensorMap* m = idx == 65 ? &tm_wg : &tm_wu;
                    tma2d(dst, m, cta * FC, 0, bar, pol);
                    tma2d(dst + 16384, m, cta * FC, 256, bar, pol);
                } else {
#pragma unroll
                    for (int cb = 0; cb < 8; cb++) tma2d(dst + cb * 4096, &tm_wd, cb * 64, cta * FC, bar, pol);
                }
            };
            int st = 0, ph = 1, st2 = (NST - MAXFLY) % NST, ph2 = 0;
            for (int idx = 0; idx < NIDX; idx++) {
                if (idx >= NST) {
                    mbar_wait(bar_empty + 8 * st, ph);
                    mbar_wait(bar_full + 8 * st2, ph2);
                    if (++st2 == NST) { st2 = 0; ph2 ^= 1; }
                }
                const uint32_t bar = bar_full + 8 * st;
                mbar_expect_tx(bar, TILE_BYTES);
                tma2d(sbase + SM_RING + st * TILE_BYTES, (idx & 1) ? &tm_v : &tm_k, 0,
                      row0 + (idx >> 1) * (8 * TILE_KEYS * 2), bar, pol);
                if (idx == 1) {
                    asm volatile("prefetch.tensormap [%0];" :: "l"(&tm_wo) : "memory");
                    asm volatile("prefetch.tensormap [%0];" :: "l"(&tm_wg) : "memory");
                    asm volatile("prefetch.tensormap [%0];" :: "l"(&tm_wu) : "memory");
                    asm volatile("prefetch.tensormap [%0];" :: "l"(&tm_wd) : "memory");
                }
                if (++st == NST) { st = 0; ph ^= 1; }
                if (idx == WO_AT) issue_w(64);
            }
            if (is_ffn) { issue_w(65); issue_w(66); issue_w(67); }
        }
        return;
    }

    TS(0);
    uint4 wm1[2], wm2[2][2], wqr[8];
    {
        const __nv_bfloat16* wm = p.w_mod + (size_t)tid * (6 * D);
        wm1[0] = ldg_stream(wm + 8 * cta);
        wm1[1] = ldg_stream(wm + (size_t)256 * (6 * D) + 8 * cta);
        const __nv_bfloat16* wq = p.wq + (size_t)(8 * (tid >> 2)) * (HQ * DH) + hkv * 512 + 32 * j16 + 8 * (tid & 3);
#pragma unroll
        for (int i = 0; i < 8; i++) wqr[i] = ldg_stream(wq + (size_t)i * (HQ * DH));
#pragma unroll
        for (int r = 0; r < 2; r++)
#pragma unroll
            for (int q = 0; q < 2; q++) wm2[r][q] = ldg_stream(wm + (size_t)r * 256 * (6 * D) + 2 * D + 16 * cta + 8 * q);
    }
    unsigned tag;
    asm volatile("ld.relaxed.gpu.global.u32 %0, [%1];" : "=r"(tag) : "l"(&g_epoch) : "memory");
    float sc[2][2];
    uint32_t xw[2];
#pragma unroll
    for (int b = 0; b < 2; b++) {
#pragma unroll
        for (int r = 0; r < 2; r++) {
            float cv = bfld(p.c + b * D + tid + 256 * r);
            sc[b][r] = bfr(cv / (1.f + __expf(-cv)));
        }
        xw[b] = *reinterpret_cast<const uint32_t*>(p.x + b * D + 2 * tid);
    }
    {
        uint4* m = reinterpret_cast<uint4*>(&g_mail) + cta * 320;
        m[tid] = make_uint4(0, 0, 0, 0);
        if (tid < 64) m[256 + tid] = make_uint4(0, 0, 0, 0);
    }
    tag += 1;

    float* scr = reinterpret_cast<float*>(smem + SM_SCR);
    float nrm[2][2];
    {
        float* st = scr + 2048;
        float xv[2][2], s[2];
#pragma unroll
        for (int b = 0; b < 2; b++) { xv[b][0] = bf_lo(xw[b]); xv[b][1] = bf_hi(xw[b]); s[b] = xv[b][0] + xv[b][1]; }
#pragma unroll
        for (int o = 16; o; o >>= 1) { s[0] += __shfl_xor_sync(~0u, s[0], o); s[1] += __shfl_xor_sync(~0u, s[1], o); }
        if (lane == 0) { st[warp * 2] = s[0]; st[warp * 2 + 1] = s[1]; }
        cons_bar();
        float mean[2] = {0.f, 0.f};
#pragma unroll
        for (int w = 0; w < 8; w++) { mean[0] += st[w * 2]; mean[1] += st[w * 2 + 1]; }
        mean[0] *= (1.f / D); mean[1] *= (1.f / D);
#pragma unroll
        for (int b = 0; b < 2; b++) {
            float d0 = xv[b][0] - mean[b], d1 = xv[b][1] - mean[b];
            s[b] = d0 * d0 + d1 * d1;
        }
#pragma unroll
        for (int o = 16; o; o >>= 1) { s[0] += __shfl_xor_sync(~0u, s[0], o); s[1] += __shfl_xor_sync(~0u, s[1], o); }
        if (lane == 0) { st[16 + warp * 2] = s[0]; st[16 + warp * 2 + 1] = s[1]; }
        cons_bar();
#pragma unroll
        for (int b = 0; b < 2; b++) {
            float var = 0.f;
#pragma unroll
            for (int w = 0; w < 8; w++) var += st[16 + w * 2 + b];
            const float mb = bfr(mean[b]);
            const float sd = bfr(sqrtf(bfr(bfr(var * (1.f / D)) + 1e-5f)));
            nrm[b][0] = bfr(bfr(xv[b][0] - mb) / sd);
            nrm[b][1] = bfr(bfr(xv[b][1] - mb) / sd);
        }
    }
    {
        float a1[16], a2[32];
#pragma unroll
        for (int b = 0; b < 2; b++) {
#pragma unroll
            for (int k = 0; k < 4; k++) {
                const uint32_t u0 = (&wm1[0].x)[k], u1 = (&wm1[1].x)[k];
                a1[b * 8 + 2 * k]     = sc[b][0] * bf_lo(u0) + sc[b][1] * bf_lo(u1);
                a1[b * 8 + 2 * k + 1] = sc[b][0] * bf_hi(u0) + sc[b][1] * bf_hi(u1);
#pragma unroll
                for (int q = 0; q < 2; q++) {
                    const uint32_t v0 = (&wm2[0][q].x)[k], v1 = (&wm2[1][q].x)[k];
                    a2[b * 16 + q * 8 + 2 * k]     = sc[b][0] * bf_lo(v0) + sc[b][1] * bf_lo(v1);
                    a2[b * 16 + q * 8 + 2 * k + 1] = sc[b][0] * bf_hi(v0) + sc[b][1] * bf_hi(v1);
                }
            }
        }
        Halve<16, 16>::run(a1, lane); Halve<8, 8>::run(a1, lane); Halve<4, 4>::run(a1, lane); Halve<2, 2>::run(a1, lane);
        a1[0] += __shfl_xor_sync(~0u, a1[0], 1);
        Halve<32, 16>::run(a2, lane); Halve<16, 8>::run(a2, lane); Halve<8, 4>::run(a2, lane);
        Halve<4, 2>::run(a2, lane); Halve<2, 1>::run(a2, lane);
        float* red = scr;
        if (!(lane & 1)) red[warp * 48 + (lane >> 1)] = a1[0];
        red[warp * 48 + 16 + lane] = a2[0];
        cons_bar();
        if (tid < 24) {
            const int i0 = tid < 8 ? tid : 16 + (tid - 8), st = tid < 8 ? 8 : 16;
            float s0 = 0.f, s1 = 0.f;
#pragma unroll
            for (int w = 0; w < 8; w++) { s0 += red[w * 48 + i0]; s1 += red[w * 48 + i0 + st]; }
            const int col = tid < 8 ? 8 * cta + tid : 2 * D + 16 * cta + (tid - 8);
            __threadfence();
            st_mail8(&g_mod[col], make_uint2(pack_bf16(s0, s1), tag));
        }
    }
    TS(1);
    const int rr = is_red ? cta - RED0 : tid >> 2, ri = is_red ? (lane & 3) : tid & 3;
    const int colA = 16 * (rr >> 1) + 4 * (rr & 1) + ri, colB = colA + 8;
    uint32_t mA0 = 0, mB0 = 0, mA1 = 0, mB1 = 0;
    {
        unsigned spins = 0;
        uint4 sa = ld_mail16(&g_mod[2 * tid]), ca = ld_mail16(&g_mod[D + 2 * tid]);
        while (sa.y != tag || sa.w != tag) { spin_guard(spins); __nanosleep(64); sa = ld_mail16(&g_mod[2 * tid]); }
        while (ca.y != tag || ca.w != tag) { spin_guard(spins); __nanosleep(64); ca = ld_mail16(&g_mod[D + 2 * tid]); }
        float* hs = scr + 512;
        const float h00 = bfr(bfr(nrm[0][0] * bfr(1.f + bf_lo(ca.x))) + bf_lo(sa.x));
        const float h01 = bfr(bfr(nrm[0][1] * bfr(1.f + bf_lo(ca.z))) + bf_lo(sa.z));
        const float h10 = bfr(bfr(nrm[1][0] * bfr(1.f + bf_hi(ca.x))) + bf_hi(sa.x));
        const float h11 = bfr(bfr(nrm[1][1] * bfr(1.f + bf_hi(ca.z))) + bf_hi(sa.z));
        *reinterpret_cast<float2*>(hs + 2 * tid)     = make_float2(h00, h01);
        *reinterpret_cast<float2*>(hs + D + 2 * tid) = make_float2(h10, h11);
        if (is_ffn || is_red) {
            const int o0 = is_ffn ? 3 * D : 2 * D, o1 = is_ffn ? 4 * D : 5 * D;
            uint2 a0 = ld_mail8(&g_mod[o0 + colA]), b0 = ld_mail8(&g_mod[o0 + colB]);
            uint2 a1 = ld_mail8(&g_mod[o1 + colA]), b1 = ld_mail8(&g_mod[o1 + colB]);
            while (a0.y != tag) { spin_guard(spins); __nanosleep(64); a0 = ld_mail8(&g_mod[o0 + colA]); }
            while (b0.y != tag) { spin_guard(spins); __nanosleep(64); b0 = ld_mail8(&g_mod[o0 + colB]); }
            while (a1.y != tag) { spin_guard(spins); __nanosleep(64); a1 = ld_mail8(&g_mod[o1 + colA]); }
            while (b1.y != tag) { spin_guard(spins); __nanosleep(64); b1 = ld_mail8(&g_mod[o1 + colB]); }
            mA0 = a0.x; mB0 = b0.x; mA1 = a1.x; mB1 = b1.x;
        }
        __threadfence();
        cons_bar();
    }
    TS(2);
    {
        const float* hs = scr + 512;
        float a[16];
#pragma unroll
        for (int i = 0; i < 16; i++) a[i] = 0.f;
        const int r0 = 8 * (tid >> 2);
#pragma unroll
        for (int b = 0; b < 2; b++) {
            const float4 ha = *reinterpret_cast<const float4*>(hs + b * D + r0);
            const float4 hb = *reinterpret_cast<const float4*>(hs + b * D + r0 + 4);
            const float hv[8] = {ha.x, ha.y, ha.z, ha.w, hb.x, hb.y, hb.z, hb.w};
#pragma unroll
            for (int i = 0; i < 8; i++)
#pragma unroll
                for (int k = 0; k < 4; k++) {
                    const uint32_t u = (&wqr[i].x)[k];
                    a[b * 8 + 2 * k]     += hv[i] * bf_lo(u);
                    a[b * 8 + 2 * k + 1] += hv[i] * bf_hi(u);
                }
        }
        Halve<16, 16>::run(a, lane); Halve<8, 8>::run(a, lane); Halve<4, 4>::run(a, lane);
        float* red = scr + 1536;
        *reinterpret_cast<float2*>(red + warp * 64 + (lane >> 4) * 32 + 8 * (lane & 3) + 4 * ((lane >> 3) & 1) + 2 * ((lane >> 2) & 1))
            = make_float2(a[0], a[1]);
        cons_bar();
        if (tid < 32) {
            float s0 = 0.f, s1 = 0.f;
#pragma unroll
            for (int w = 0; w < 8; w++) { s0 += red[w * 64 + tid]; s1 += red[w * 64 + 32 + tid]; }
            st_mail8(&g_q[hkv * 512 + 32 * j16 + tid], make_uint2(pack_bf16(s0, s1), tag));
        }
    }
    TS(3);
    uint32_t qf[8][2];
    {
        unsigned spins = 0;
        const uint2* src = &g_q[hkv * 512 + 2 * tid];
        uint4 v = ld_mail16(src);
        while (v.y != tag || v.w != tag) { spin_guard(spins); __nanosleep(32); v = ld_mail16(src); }
        uint32_t* qs = reinterpret_cast<uint32_t*>(scr + 2176);
        const uint32_t w = bat ? ((v.x >> 16) | (v.z & 0xffff0000u)) : ((v.x & 0xffffu) | (v.z << 16));
        qs[(tid >> 6) * 68 + (tid & 63)] = w;
        cons_bar();
        const int g = lane >> 2, t = lane & 3;
#pragma unroll
        for (int ks = 0; ks < 8; ks++) {
            qf[ks][0] = g < 4 ? qs[g * 68 + 8 * ks + t] : 0u;
            qf[ks][1] = g < 4 ? qs[g * 68 + 8 * ks + 4 + t] : 0u;
        }
    }
    asm volatile("bar.sync 2, 288;" ::: "memory");
    TS(4);

    float oacc[8][4];
#pragma unroll
    for (int i = 0; i < 8; i++) { oacc[i][0] = oacc[i][1] = oacc[i][2] = oacc[i][3] = 0.f; }
    float m0 = -INFINITY, m1 = -INFINITY, l0 = 0.f, l1 = 0.f;
    {
        const int keyK = warp * 16 + (lane & 7) + 8 * ((lane >> 3) & 1);
        const uint32_t kA = keyK * 256, kX = (((lane >> 4) ^ (2 * (keyK & 3))) << 4);
        const int keyV = warp * 16 + (lane & 7) + 8 * (lane >> 4);
        const uint32_t vA = keyV * 256, vX = ((((lane >> 3) & 1) ^ (2 * (keyV & 3))) << 4);
        int st = 0, ph = 0;
        for (int it = 0; it < NTILES; it++) {
            uint32_t base = sbase + SM_RING + st * TILE_BYTES + kA;
            mbar_wait(bar_full + 8 * st, ph);
            float s0[4] = {0.f, 0.f, 0.f, 0.f}, s1[4] = {0.f, 0.f, 0.f, 0.f};
#pragma unroll
            for (int ks = 0; ks < 8; ks++) {
                uint32_t a[4];
                const int hf = ks >> 2;
                ldsm4(a, base + hf * 128 + ((((2 * (ks & 3)) ^ hf) << 4) ^ kX));
                if (ks & 1) mma16816(s1, a, qf[ks][0], qf[ks][1]); else mma16816(s0, a, qf[ks][0], qf[ks][1]);
            }
            __syncwarp();
            if (lane == 0) mbar_arrive(bar_empty + 8 * st);
            if (++st == NST) { st = 0; ph ^= 1; }
            const uint32_t ra = pack_bf16(s0[0] + s1[0], s0[1] + s1[1]), rb = pack_bf16(s0[2] + s1[2], s0[3] + s1[3]);
            const uint32_t sa = pack_bf16(bf_lo(ra) * SCALE, bf_hi(ra) * SCALE), sb = pack_bf16(bf_lo(rb) * SCALE, bf_hi(rb) * SCALE);
            const float c0 = bf_lo(sa), c1 = bf_hi(sa), c2 = bf_lo(sb), c3 = bf_hi(sb);
            float x0 = fmaxf(c0, c2), x1 = fmaxf(c1, c3);
#pragma unroll
            for (int o = 4; o <= 16; o <<= 1) {
                x0 = fmaxf(x0, __shfl_xor_sync(~0u, x0, o));
                x1 = fmaxf(x1, __shfl_xor_sync(~0u, x1, o));
            }
            if (__any_sync(~0u, x0 > m0 || x1 > m1)) {
                const float n0 = fmaxf(m0, x0), n1 = fmaxf(m1, x1);
                const float f0 = ex2((m0 - n0) * LOG2E), f1 = ex2((m1 - n1) * LOG2E);
                m0 = n0; m1 = n1; l0 *= f0; l1 *= f1;
#pragma unroll
                for (int i = 0; i < 8; i++) { oacc[i][0] *= f0; oacc[i][1] *= f1; oacc[i][2] *= f0; oacc[i][3] *= f1; }
            }
            const float p0 = ex2((c0 - m0) * LOG2E), p1 = ex2((c1 - m1) * LOG2E);
            const float p2 = ex2((c2 - m0) * LOG2E), p3 = ex2((c3 - m1) * LOG2E);
            l0 += p0 + p2; l1 += p1 + p3;
            const uint32_t b0 = movtrans(pack_bf16(p0, p1)), b1 = movtrans(pack_bf16(p2, p3));
            base = sbase + SM_RING + st * TILE_BYTES + vA;
            mbar_wait(bar_full + 8 * st, ph);
#pragma unroll
            for (int i = 0; i < 8; i++) {
                uint32_t a[4];
                const int hf = i >> 2;
                ldsm4t(a, base + hf * 128 + ((((2 * (i & 3)) ^ hf) << 4) ^ vX));
                mma16816(oacc[i], a, b0, b1);
            }
            __syncwarp();
            if (lane == 0) mbar_arrive(bar_empty + 8 * st);
            if (++st == NST) { st = 0; ph ^= 1; }
        }
    }
    TS(5);

    const int g = lane >> 2, t = lane & 3;
    {
#pragma unroll
        for (int o = 4; o <= 16; o <<= 1) { l0 += __shfl_xor_sync(~0u, l0, o); l1 += __shfl_xor_sync(~0u, l1, o); }
        float* ro = scr + warp * 576;
        float2* ml = reinterpret_cast<float2*>(smem + SM_ML);
        if (t < 2) {
#pragma unroll
            for (int i = 0; i < 8; i++) {
                const int d = 16 * i + g;
                *reinterpret_cast<float2*>(ro + d * 4 + 2 * t + 4 * (d >> 3))             = make_float2(oacc[i][0], oacc[i][1]);
                *reinterpret_cast<float2*>(ro + (d + 8) * 4 + 2 * t + 4 * ((d + 8) >> 3)) = make_float2(oacc[i][2], oacc[i][3]);
            }
            if (g == 0) { ml[warp * 4 + 2 * t] = make_float2(m0, l0); ml[warp * 4 + 2 * t + 1] = make_float2(m1, l1); }
        }
        cons_bar();
        const int hd = tid & 3, dg = tid >> 2;
        float2 mw[8];
        float ov[8][2];
        const int a0 = (2 * dg) * 4 + hd + 4 * ((2 * dg) >> 3);
#pragma unroll
        for (int w = 0; w < 8; w++) {
            mw[w] = ml[w * 4 + hd];
            ov[w][0] = scr[w * 576 + a0]; ov[w][1] = scr[w * 576 + a0 + 4];
        }
        float M = mw[0].x;
#pragma unroll
        for (int w = 1; w < 8; w++) M = fmaxf(M, mw[w].x);
        float L = 0.f, o0 = 0.f, o1 = 0.f;
#pragma unroll
        for (int w = 0; w < 8; w++) {
            const float f = ex2((mw[w].x - M) * LOG2E);
            L += f * mw[w].y; o0 += f * ov[w][0]; o1 += f * ov[w][1];
        }
        float* dst = g_mail.h1 + ((hkv * 16 + j16) * 4 + hd) * H1_HS;
        st_mail8(dst + 2 * dg, make_uint2(nz(o0), nz(o1)));
        if (dg == 0) st_mail8(dst + 128, make_uint2(nz(M), nz(L)));
    }
    TS(6);
    uint32_t* os = reinterpret_cast<uint32_t*>(smem + SM_SMALL);
    {
        uint32_t wa[8][4];
        mbar_wait(bar_full + 8 * (64 % NST), (64 / NST) & 1);
        {
            const uint32_t wb = sbase + SM_RING + (64 % NST) * TILE_BYTES + (warp >> 2) * 16384;
            const int mi = lane >> 3, r = lane & 7;
            const int chunk = 2 * (warp & 3) + (mi & 1);
#pragma unroll
            for (int ks = 0; ks < 8; ks++) {
                const int row = 32 * (ks >> 1) + 8 * (r >> 1) + 4 * (ks & 1) + 2 * (mi >> 1) + (r & 1);
                ldsm4t(wa[ks], wb + row * 128 + ((chunk ^ (row & 7)) << 4));
            }
        }
        TS(7);
        if (tid < 64) {
            const int b = tid >> 5, k = tid & 31, hh = j16 >> 2;
            const float* src = g_mail.h1 + ((hkv * 16 + b * 8) * 4 + hh) * H1_HS;
            uint4 ov[8]; uint2 mv[8];
#pragma unroll
            for (int s = 0; s < 8; s++) { ov[s] = ld_mail16(src + s * 4 * H1_HS + 4 * k); mv[s] = ld_mail8(src + s * 4 * H1_HS + 128); }
            unsigned spins = 0;
#pragma unroll
            for (int s = 0; s < 8; s++) {
                while (!full4(ov[s])) { spin_guard(spins); ov[s] = ld_mail16(src + s * 4 * H1_HS + 4 * k); }
                while (!(mv[s].x && mv[s].y)) { spin_guard(spins); mv[s] = ld_mail8(src + s * 4 * H1_HS + 128); }
            }
            float M = __uint_as_float(mv[0].x);
#pragma unroll
            for (int s = 1; s < 8; s++) M = fmaxf(M, __uint_as_float(mv[s].x));
            float L = 0.f, o0 = 0.f, o1 = 0.f, o2 = 0.f, o3 = 0.f;
#pragma unroll
            for (int s = 0; s < 8; s++) {
                const float f = ex2((__uint_as_float(mv[s].x) - M) * LOG2E);
                L += f * __uint_as_float(mv[s].y);
                o0 += f * __uint_as_float(ov[s].x); o1 += f * __uint_as_float(ov[s].y);
                o2 += f * __uint_as_float(ov[s].z); o3 += f * __uint_as_float(ov[s].w);
            }
            const float inv = 1.f / L;
            *reinterpret_cast<uint2*>(os + b * 64 + 2 * k) = make_uint2(pack_bf16(o0 * inv, o1 * inv), pack_bf16(o2 * inv, o3 * inv));
        }
        cons_bar();
        TS(8);
        float c0[4] = {0.f, 0.f, 0.f, 0.f}, c1[4] = {0.f, 0.f, 0.f, 0.f}, c2[4] = {0.f, 0.f, 0.f, 0.f}, c3[4] = {0.f, 0.f, 0.f, 0.f};
        uint4 bq[4];
#pragma unroll
        for (int kk = 0; kk < 4; kk++)
            bq[kk] = g < 2 ? *reinterpret_cast<const uint4*>(os + g * 64 + 16 * kk + 4 * t) : make_uint4(0, 0, 0, 0);
        mma16816(c0, wa[0], bq[0].x, bq[0].y); mma16816(c1, wa[1], bq[0].z, bq[0].w);
        mma16816(c2, wa[2], bq[1].x, bq[1].y); mma16816(c3, wa[3], bq[1].z, bq[1].w);
        mma16816(c0, wa[4], bq[2].x, bq[2].y); mma16816(c1, wa[5], bq[2].z, bq[2].w);
        mma16816(c2, wa[6], bq[3].x, bq[3].y); mma16816(c3, wa[7], bq[3].z, bq[3].w);
        if (t == 0) {
            const int h = hkv * 4 + (j16 >> 2), mt = (j16 & 3) * 8 + warp;
            const int r = 2 * mt + (g >> 2);
            st_mail16(&g_mail.rs1[(r * 32 + h) * 4 + (g & 3)],
                      make_uint4(nz((c0[0] + c1[0]) + (c2[0] + c3[0])), nz((c0[1] + c1[1]) + (c2[1] + c3[1])),
                                 nz((c0[2] + c1[2]) + (c2[2] + c3[2])), nz((c0[3] + c1[3]) + (c2[3] + c3[3]))));
        }
    }
    TS(9);

    if (is_red) {
        if (warp == 0) {
            const int r = cta - RED0, ps = lane >> 2;
            const float xA0 = bfld(p.x + colA), xA1 = bfld(p.x + D + colA), xB0 = bfld(p.x + colB), xB1 = bfld(p.x + D + colB);
            uint4 v[4];
            const float4* src = &g_mail.rs1[(r * 32 + ps) * 4 + ri];
#pragma unroll
            for (int j = 0; j < 4; j++) v[j] = ld_mail16(src + j * 32);
            unsigned spins = 0;
#pragma unroll
            for (int j = 0; j < 4; j++) while (!full4(v[j])) { spin_guard(spins); v[j] = ld_mail16(src + j * 32); }
            float s[4];
#pragma unroll
            for (int k = 0; k < 4; k++)
                s[k] = (__uint_as_float((&v[0].x)[k]) + __uint_as_float((&v[1].x)[k])) + (__uint_as_float((&v[2].x)[k]) + __uint_as_float((&v[3].x)[k]));
#pragma unroll
            for (int o = 4; o <= 16; o <<= 1)
#pragma unroll
                for (int k = 0; k < 4; k++) s[k] += __shfl_xor_sync(~0u, s[k], o);
            const float yA0 = bfr(xA0 + bfr(bf_lo(mA0) * bfr(s[0]))), yA1 = bfr(xA1 + bfr(bf_hi(mA0) * bfr(s[1])));
            const float yB0 = bfr(xB0 + bfr(bf_lo(mB0) * bfr(s[2]))), yB1 = bfr(xB1 + bfr(bf_hi(mB0) * bfr(s[3])));
            uint32_t wA = pack_bf16(yA0, yA1), wB = pack_bf16(yB0, yB1);
            st_mail8(&g_mail.ag[(ps * 64 + r) * 4 + ri], make_uint2(wA ? wA : 0x80000000u, wB ? wB : 0x80000000u));
            TSW(10);
            uint4 f[7];
            const float4* src3 = &g_mail.rs3[(r * NFFN + ps) * 4 + ri];
#pragma unroll
            for (int j = 0; j < 7; j++) f[j] = ld_mail16(src3 + j * 32);
#pragma unroll
            for (int j = 0; j < 7; j++) while (!full4(f[j])) { spin_guard(spins); f[j] = ld_mail16(src3 + j * 32); }
#pragma unroll
            for (int k = 0; k < 4; k++) {
                s[k] = 0.f;
#pragma unroll
                for (int j = 0; j < 7; j++) s[k] += __uint_as_float((&f[j].x)[k]);
            }
#pragma unroll
            for (int o = 4; o <= 16; o <<= 1)
#pragma unroll
                for (int k = 0; k < 4; k++) s[k] += __shfl_xor_sync(~0u, s[k], o);
            if (ps == 0) {
                p.out[colA]     = __float2bfloat16(yA0 + bfr(bf_lo(mA1) * bfr(s[0])));
                p.out[D + colA] = __float2bfloat16(yA1 + bfr(bf_hi(mA1) * bfr(s[1])));
                p.out[colB]     = __float2bfloat16(yB0 + bfr(bf_lo(mB1) * bfr(s[2])));
                p.out[D + colB] = __float2bfloat16(yB1 + bfr(bf_hi(mB1) * bfr(s[3])));
            }
            TSW(11);
            if (cta == RED0 && lane == 0)
                asm volatile("st.relaxed.gpu.global.u32 [%0], %1;" :: "l"(&g_epoch), "r"(tag) : "memory");
        }
    } else if (is_ffn) {
        const int mat = warp >> 2, kq = warp & 3;
        uint32_t ga[2][8][4], da[4][2][4];
        {
            const int idx = 65 + mat;
            mbar_wait(bar_full + 8 * (idx % NST), (idx / NST) & 1);
            const uint32_t wb = sbase + SM_RING + (idx % NST) * TILE_BYTES;
            const int mi = lane >> 3, r = lane & 7;
#pragma unroll
            for (int ks = 0; ks < 8; ks++) {
                const int row = 128 * kq + 32 * (ks >> 1) + 8 * (r >> 1) + 4 * (ks & 1) + 2 * (mi >> 1) + (r & 1);
#pragma unroll
                for (int mt = 0; mt < 2; mt++) {
                    const int chunk = 2 * mt + (mi & 1);
                    ldsm4t(ga[mt][ks], wb + row * 64 + ((chunk ^ ((row >> 1) & 3)) << 4));
                }
            }
            mbar_wait(bar_full + 8 * (67 % NST), (67 / NST) & 1);
            const uint32_t db = sbase + SM_RING + (67 % NST) * TILE_BYTES + warp * 4096;
#pragma unroll
            for (int u = 0; u < 2; u++) {
                const int row = 8 * (r >> 1) + 4 * u + 2 * (mi >> 1) + (r & 1);
#pragma unroll
                for (int jm = 0; jm < 4; jm++) {
                    const int chunk = 2 * jm + (mi & 1);
                    ldsm4t(da[jm][u], db + row * 128 + ((chunk ^ (row & 7)) << 4));
                }
            }
        }
        TS(10);
        {
            const uint2* src = &g_mail.ag[(cta & (NREP - 1)) * 256 + tid];
            uint2 v = ld_mail8(src);
            unsigned spins = 0;
            while (!(v.x && v.y)) { spin_guard(spins); v = ld_mail8(src); }
            TS(11);
            const float xa[2] = {bf_lo(v.x), bf_hi(v.x)}, xb[2] = {bf_lo(v.y), bf_hi(v.y)};
            float sh[2], s1[2], s2[2];
#pragma unroll
            for (int b = 0; b < 2; b++) {
                sh[b] = __shfl_sync(~0u, xa[b], 0);
                const float d0 = xa[b] - sh[b], d1 = xb[b] - sh[b];
                s1[b] = d0 + d1; s2[b] = d0 * d0 + d1 * d1;
            }
#pragma unroll
            for (int o = 16; o; o >>= 1)
#pragma unroll
                for (int b = 0; b < 2; b++) { s1[b] += __shfl_xor_sync(~0u, s1[b], o); s2[b] += __shfl_xor_sync(~0u, s2[b], o); }
            float4* stt = reinterpret_cast<float4*>(smem + SM_SMALL + 2048);
            if (lane == 0) {
                const float d0 = s1[0] * (1.f / 64), d1 = s1[1] * (1.f / 64);
                stt[warp] = make_float4(sh[0] + d0, s2[0] - s1[0] * d0, sh[1] + d1, s2[1] - s1[1] * d1);
            }
            cons_bar();
            float4 sw[8];
#pragma unroll
            for (int w = 0; w < 8; w++) sw[w] = stt[w];
            float mean0 = 0.f, mean1 = 0.f;
#pragma unroll
            for (int w = 0; w < 8; w++) { mean0 += sw[w].x; mean1 += sw[w].z; }
            mean0 *= 0.125f; mean1 *= 0.125f;
            float q0 = 0.f, q1 = 0.f;
#pragma unroll
            for (int w = 0; w < 8; w++) {
                const float e0 = sw[w].x - mean0, e1 = sw[w].z - mean1;
                q0 += sw[w].y + 64.f * e0 * e0; q1 += sw[w].w + 64.f * e1 * e1;
            }
            const float mb0 = bfr(mean0), mb1 = bfr(mean1);
            const float sd0 = bfr(sqrtf(bfr(bfr(fmaxf(q0, 0.f) * (1.f / D)) + 1e-5f)));
            const float sd1 = bfr(sqrtf(bfr(bfr(fmaxf(q1, 0.f) * (1.f / D)) + 1e-5f)));
            const float hA0 = bfr(bfr(bfr(xa[0] - mb0) / sd0) * bfr(1.f + bf_lo(mA1))) + bf_lo(mA0);
            const float hA1 = bfr(bfr(bfr(xa[1] - mb1) / sd1) * bfr(1.f + bf_hi(mA1))) + bf_hi(mA0);
            const float hB0 = bfr(bfr(bfr(xb[0] - mb0) / sd0) * bfr(1.f + bf_lo(mB1))) + bf_lo(mB0);
            const float hB1 = bfr(bfr(bfr(xb[1] - mb1) / sd1) * bfr(1.f + bf_hi(mB1))) + bf_hi(mB0);
            __nv_bfloat16* h2 = reinterpret_cast<__nv_bfloat16*>(smem + SM_SMALL);
            h2[colA] = __float2bfloat16(hA0); h2[D + colA] = __float2bfloat16(hA1);
            h2[colB] = __float2bfloat16(hB0); h2[D + colB] = __float2bfloat16(hB1);
            cons_bar();
        }
        TS(12);
        float* red = scr;
        {
            const uint32_t* h2w = reinterpret_cast<const uint32_t*>(smem + SM_SMALL);
            uint4 bq[4];
#pragma unroll
            for (int kk = 0; kk < 4; kk++)
                bq[kk] = g < 2 ? *reinterpret_cast<const uint4*>(h2w + g * 256 + 64 * kq + 16 * kk + 4 * t) : make_uint4(0, 0, 0, 0);
            float c[2][2][4];
#pragma unroll
            for (int mt = 0; mt < 2; mt++)
#pragma unroll
                for (int u = 0; u < 2; u++) c[mt][u][0] = c[mt][u][1] = c[mt][u][2] = c[mt][u][3] = 0.f;
#pragma unroll
            for (int kk = 0; kk < 4; kk++)
#pragma unroll
                for (int mt = 0; mt < 2; mt++) {
                    mma16816(c[mt][0], ga[mt][2 * kk], bq[kk].x, bq[kk].y);
                    mma16816(c[mt][1], ga[mt][2 * kk + 1], bq[kk].z, bq[kk].w);
                }
            if (t == 0) {
#pragma unroll
                for (int mt = 0; mt < 2; mt++) {
                    *reinterpret_cast<float2*>(red + (warp * 32 + mt * 16 + g) * 2)     = make_float2(c[mt][0][0] + c[mt][1][0], c[mt][0][1] + c[mt][1][1]);
                    *reinterpret_cast<float2*>(red + (warp * 32 + mt * 16 + 8 + g) * 2) = make_float2(c[mt][0][2] + c[mt][1][2], c[mt][0][3] + c[mt][1][3]);
                }
            }
            cons_bar();
            __nv_bfloat16* as = reinterpret_cast<__nv_bfloat16*>(smem + SM_SMALL + 3072);
            if (tid < 64) {
                const int f = tid >> 1, b = tid & 1;
                float gs = 0.f, us = 0.f;
#pragma unroll
                for (int k = 0; k < 4; k++) { gs += red[(k * 32 + f) * 2 + b]; us += red[((4 + k) * 32 + f) * 2 + b]; }
                gs = bfr(gs); us = bfr(us);
                const float y = 0.7978845608028654f * (gs + 0.044715f * gs * gs * gs);
                const float ge = bfr(gs / (1.f + __expf(-2.f * y)));
                as[b * 32 + f] = __float2bfloat16(ge * us);
            }
            cons_bar();
            const uint4 ab = g < 2 ? *reinterpret_cast<const uint4*>(as + g * 32 + 8 * t) : make_uint4(0, 0, 0, 0);
#pragma unroll
            for (int jm = 0; jm < 4; jm++) {
                float e0[4] = {0.f, 0.f, 0.f, 0.f}, e1[4] = {0.f, 0.f, 0.f, 0.f};
                mma16816(e0, da[jm][0], ab.x, ab.y);
                mma16816(e1, da[jm][1], ab.z, ab.w);
                if (t == 0) {
                    const int r = 2 * (4 * warp + jm) + (g >> 2);
                    st_mail16(&g_mail.rs3[(r * NFFN + cta) * 4 + (g & 3)],
                              make_uint4(nz(e0[0] + e1[0]), nz(e0[1] + e1[1]), nz(e0[2] + e1[2]), nz(e0[3] + e1[3])));
                }
            }
        }
        TS(13);
    }
}

typedef CUresult (*EncodeTiledFn)(CUtensorMap*, CUtensorMapDataType, cuuint32_t, void*, const cuuint64_t*, const cuuint64_t*,
                                  const cuuint32_t*, const cuuint32_t*, CUtensorMapInterleave, CUtensorMapSwizzle,
                                  CUtensorMapL2promotion, CUtensorMapFloatOOBfill);

CUtensorMap make_map(EncodeTiledFn enc, const void* ptr, uint64_t inner, uint64_t rows, uint64_t pitch_bytes,
                     uint32_t box_inner, uint32_t box_rows, CUtensorMapSwizzle sw, CUtensorMapL2promotion prom) {
    CUtensorMap m;
    cuuint64_t gd[2] = {inner, rows};
    cuuint64_t gs[1] = {pitch_bytes};
    cuuint32_t bd[2] = {box_inner, box_rows};
    cuuint32_t es[2] = {1, 1};
    enc(&m, CU_TENSOR_MAP_DATA_TYPE_BFLOAT16, 2, const_cast<void*>(ptr), gd, gs, bd, es,
        CU_TENSOR_MAP_INTERLEAVE_NONE, sw, prom, CU_TENSOR_MAP_FLOAT_OOB_FILL_NONE);
    return m;
}

}

extern "C" void kernel_launch(void* const* d_in, const int* in_sizes, int n_in, void* d_out, int out_size) {
    (void)in_sizes; (void)n_in; (void)out_size;
    EncodeTiledFn enc = nullptr;
    cudaDriverEntryPointQueryResult qr;
    cudaGetDriverEntryPoint("cuTensorMapEncodeTiled", reinterpret_cast<void**>(&enc), cudaEnableDefault, &qr);
    const uint64_t kv_rows = (uint64_t)2 * HKV * SK * 2;
    CUtensorMap tk = make_map(enc, d_in[1], 64, kv_rows, 128, 64, 256, CU_TENSOR_MAP_SWIZZLE_128B, CU_TENSOR_MAP_L2_PROMOTION_NONE);
    CUtensorMap tv = make_map(enc, d_in[2], 64, kv_rows, 128, 64, 256, CU_TENSOR_MAP_SWIZZLE_128B, CU_TENSOR_MAP_L2_PROMOTION_NONE);
    CUtensorMap to = make_map(enc, d_in[4], D, HQ * DH, D * 2, 64, 128, CU_TENSOR_MAP_SWIZZLE_128B, CU_TENSOR_MAP_L2_PROMOTION_L2_256B);
    CUtensorMap tg = make_map(enc, d_in[6], FF, D, FF * 2, FC, 256, CU_TENSOR_MAP_SWIZZLE_64B, CU_TENSOR_MAP_L2_PROMOTION_L2_128B);
    CUtensorMap tu = make_map(enc, d_in[7], FF, D, FF * 2, FC, 256, CU_TENSOR_MAP_SWIZZLE_64B, CU_TENSOR_MAP_L2_PROMOTION_L2_128B);
    CUtensorMap td = make_map(enc, d_in[8], D, FF, D * 2, 64, FC, CU_TENSOR_MAP_SWIZZLE_128B, CU_TENSOR_MAP_L2_PROMOTION_L2_256B);
    Params p;
    p.x = (const __nv_bfloat16*)d_in[0];
    p.wq = (const __nv_bfloat16*)d_in[3];
    p.c = (const __nv_bfloat16*)d_in[9];
    p.w_mod = (const __nv_bfloat16*)d_in[10];
    p.out = (__nv_bfloat16*)d_out;
    cudaFuncSetAttribute(fused_kernel, cudaFuncAttributeMaxDynamicSharedMemorySize, SM_ALLOC);
    fused_kernel<<<NCTA, NTHR, SM_ALLOC>>>(p, tk, tv, to, tg, tu, td);
}
```

```cpp
#include <cuda_runtime.h>
#include <cuda_bf16.h>
#include <cuda.h>
#include <stdint.h>

namespace {

constexpr int D      = 512;
constexpr int HQ     = 32;
constexpr int HKV    = 8;
constexpr int SK     = 32768;
constexpr int DH     = 128;
constexpr int FF     = 1792;
constexpr int NCTA   = 128;
constexpr int NTHR   = 320;
constexpr int TILE_KEYS  = 128;
constexpr int TILE_BYTES = TILE_KEYS * DH * 2;
constexpr int NST    = 6;
constexpr int NTILES = (SK / 8) / TILE_KEYS;
constexpr int IDX0   = 2;
constexpr int NIDX   = IDX0 + 2 * NTILES;
constexpr int IDX_WO = NIDX, IDX_WG = NIDX + 1, IDX_WU = NIDX + 2, IDX_WD = NIDX + 3;
constexpr int MAXFLY = 2;
constexpr int NFFN   = 56;
constexpr int FC     = 32;
constexpr int RED0   = 64;
constexpr int NREP   = 8;
constexpr int NREPM  = 4;
constexpr int PM2_0 = 16, PM1_0 = 48, PQ_0 = 64;

#define WO_AT 62
#define PACE_LEAD4 4
#define PACE_LAG4 1
#define WARM_AT 16
#define PROBE_WAIT 500
#define PROBE_N 16
constexpr int PROG_END = NIDX - 2;

constexpr int H1_HS = 136;
constexpr int ML_H1  = 0;
constexpr int ML_RS1 = ML_H1 + HKV * 16 * 4 * H1_HS * 4;
constexpr int ML_RS3 = ML_RS1 + 64 * 32 * 4 * 16;
constexpr int ML_AG  = ML_RS3 + 64 * NFFN * 4 * 16;
constexpr int ML_PRB = ML_AG + (NREP / 2) * 4096;
constexpr int ML_END = ML_PRB + 4096;
static_assert(ML_RS1 % 4096 == 0 && ML_RS3 % 4096 == 0 && ML_AG % 4096 == 0 && 2 * ML_END <= (2 << 20), "mailbox layout");
__device__ uint8_t g_mailraw[4 << 20];
__device__ __align__(128) uint2 g_mod1[NREPM * 2 * D];
__device__ __align__(128) uint2 g_mod2[4 * D];
__device__ __align__(128) uint2 g_q[HQ * DH];
__device__ unsigned g_epoch;
__device__ __align__(128) unsigned g_prog[32];
#define TS(i)
#define TSW(i)
#define TSB(i)
#define TS_CAL()
#define TS_START()
#define TS_DUMP()

constexpr int SM_RING   = 0;
constexpr int SM_SCR    = NST * TILE_BYTES;
constexpr int SM_ML     = SM_SCR + 18432;
constexpr int SM_SMALL  = SM_ML + 256;
constexpr int SM_CS     = SM_SMALL + 4096;
constexpr int SM_BAR    = SM_CS + 4096;
constexpr int SM_TOTAL  = SM_BAR + 128;
constexpr int SM_ALLOC  = SM_TOTAL + 1024;

constexpr unsigned SPIN_LIMIT = 1u << 24;

__device__ __forceinline__ uint32_t smem_u32(const void* p) { return (uint32_t)__cvta_generic_to_shared(p); }
__device__ __forceinline__ void mbar_init(uint32_t bar, uint32_t cnt) {
    asm volatile("mbarrier.init.shared::cta.b64 [%0], %1;" :: "r"(bar), "r"(cnt) : "memory");
}
__device__ __forceinline__ void mbar_expect_tx(uint32_t bar, uint32_t bytes) {
    asm volatile("mbarrier.arrive.expect_tx.shared::cta.b64 _, [%0], %1;" :: "r"(bar), "r"(bytes) : "memory");
}
__device__ __forceinline__ void mbar_arrive(uint32_t bar) {
    asm volatile("mbarrier.arrive.shared::cta.b64 _, [%0];" :: "r"(bar) : "memory");
}
__device__ __forceinline__ void mbar_wait(uint32_t bar, uint32_t parity) {
    uint32_t ok;
    unsigned spins = 0;
    do {
        asm volatile("{\n.reg .pred p;\nmbarrier.try_wait.parity.shared::cta.b64 p, [%1], %2;\nselp.u32 %0, 1, 0, p;\n}"
                     : "=r"(ok) : "r"(bar), "r"(parity) : "memory");
        if (++spins > SPIN_LIMIT) __trap();
    } while (!ok);
}
__device__ __forceinline__ void tma2d(uint32_t dst, const CUtensorMap* m, int c0, int c1, uint32_t bar, uint64_t pol) {
    asm volatile("cp.async.bulk.tensor.2d.shared::cluster.global.mbarrier::complete_tx::bytes.L2::cache_hint"
                 " [%0], [%1, {%3, %4}], [%2], %5;"
                 :: "r"(dst), "l"(m), "r"(bar), "r"(c0), "r"(c1), "l"(pol) : "memory");
}
__device__ __forceinline__ void ldsm4(uint32_t (&r)[4], uint32_t addr) {
    asm volatile("ldmatrix.sync.aligned.m8n8.x4.shared.b16 {%0,%1,%2,%3}, [%4];"
                 : "=r"(r[0]), "=r"(r[1]), "=r"(r[2]), "=r"(r[3]) : "r"(addr) : "memory");
}
__device__ __forceinline__ void ldsm4t(uint32_t (&r)[4], uint32_t addr) {
    asm volatile("ldmatrix.sync.aligned.m8n8.x4.trans.shared.b16 {%0,%1,%2,%3}, [%4];"
                 : "=r"(r[0]), "=r"(r[1]), "=r"(r[2]), "=r"(r[3]) : "r"(addr) : "memory");
}
__device__ __forceinline__ void mma16816(float (&c)[4], const uint32_t (&a)[4], uint32_t b0, uint32_t b1) {
    asm volatile("mma.sync.aligned.m16n8k16.row.col.f32.bf16.bf16.f32 {%0,%1,%2,%3}, {%4,%5,%6,%7}, {%8,%9}, {%0,%1,%2,%3};"
                 : "+f"(c[0]), "+f"(c[1]), "+f"(c[2]), "+f"(c[3])
                 : "r"(a[0]), "r"(a[1]), "r"(a[2]), "r"(a[3]), "r"(b0), "r"(b1));
}
__device__ __forceinline__ uint32_t movtrans(uint32_t a) {
    uint32_t d;
    asm volatile("movmatrix.sync.aligned.m8n8.trans.b16 %0, %1;" : "=r"(d) : "r"(a));
    return d;
}
template <int OFF> __device__ __forceinline__ void lds128_if(uint4& v, uint32_t addr, uint32_t pred) {
    asm volatile("{\n.reg .pred q;\nsetp.ne.u32 q, %5, 0;\n@q ld.shared.v4.u32 {%0,%1,%2,%3}, [%4+%6];\n}"
                 : "+r"(v.x), "+r"(v.y), "+r"(v.z), "+r"(v.w) : "r"(addr), "r"(pred), "n"(OFF) : "memory");
}
template <int OFF> __device__ __forceinline__ float lds32(uint32_t addr) {
    float v; asm volatile("ld.shared.f32 %0, [%1+%2];" : "=f"(v) : "r"(addr), "n"(OFF) : "memory"); return v;
}
template <int OFF> __device__ __forceinline__ float2 lds64(uint32_t addr) {
    float2 v; asm volatile("ld.shared.v2.f32 {%0,%1}, [%2+%3];" : "=f"(v.x), "=f"(v.y) : "r"(addr), "n"(OFF) : "memory"); return v;
}
template <int OFF> __device__ __forceinline__ void sts16(uint32_t addr, uint32_t v) {
    asm volatile("st.shared.u16 [%0+%1], %2;" :: "r"(addr), "n"(OFF), "h"((uint16_t)v) : "memory");
}
template <int OFF> __device__ __forceinline__ void sts32(uint32_t addr, float v) {
    asm volatile("st.shared.f32 [%0+%1], %2;" :: "r"(addr), "n"(OFF), "f"(v) : "memory");
}
template <int OFF> __device__ __forceinline__ void sts64(uint32_t addr, float a, float b) {
    asm volatile("st.shared.v2.f32 [%0+%1], {%2,%3};" :: "r"(addr), "n"(OFF), "f"(a), "f"(b) : "memory");
}
template <class T> __device__ __forceinline__ void pin(T& v) { asm volatile("" : "+r"(v)); }
__device__ __forceinline__ void pin4(uint4& v) { asm volatile("" : "+r"(v.x), "+r"(v.y), "+r"(v.z), "+r"(v.w)); }
__device__ __forceinline__ void cons_bar() { asm volatile("bar.sync 1, 256;" ::: "memory"); }
__device__ __forceinline__ float ex2(float x) { float y; asm("ex2.approx.ftz.f32 %0, %1;" : "=f"(y) : "f"(x)); return y; }
__device__ __forceinline__ float sqrt_fast(float x) { float y; asm("sqrt.approx.f32 %0, %1;" : "=f"(y) : "f"(x)); return y; }
__device__ __forceinline__ uint32_t pack_bf16(float lo, float hi) {
    uint32_t r; asm("cvt.rn.bf16x2.f32 %0, %1, %2;" : "=r"(r) : "f"(hi), "f"(lo)); return r;
}
__device__ __forceinline__ float bf_lo(uint32_t w) { return __uint_as_float(w << 16); }
__device__ __forceinline__ float bf_hi(uint32_t w) { return __uint_as_float(w & 0xffff0000u); }
__device__ __forceinline__ float bfr(float x) { return bf_lo(pack_bf16(x, 0.f)); }

__device__ __forceinline__ uint4 ld_mail16(const void* p) {
    uint4 v;
    asm volatile("{\n.reg .b128 t;\n.reg .b64 lo, hi;\nld.relaxed.gpu.global.b128 t, [%4];\nmov.b128 {lo, hi}, t;\n"
                 "mov.b64 {%0, %1}, lo;\nmov.b64 {%2, %3}, hi;\n}"
                 : "=r"(v.x), "=r"(v.y), "=r"(v.z), "=r"(v.w) : "l"(p) : "memory");
    return v;
}
__device__ __forceinline__ uint2 ld_mail8(const void* p) {
    unsigned long long v;
    asm volatile("ld.relaxed.gpu.global.b64 %0, [%1];" : "=l"(v) : "l"(p) : "memory");
    return make_uint2((uint32_t)v, (uint32_t)(v >> 32));
}
__device__ __forceinline__ void st_mail16(void* p, uint4 v) {
    asm volatile("{\n.reg .b128 t;\n.reg .b64 lo, hi;\nmov.b64 lo, {%1, %2};\nmov.b64 hi, {%3, %4};\nmov.b128 t, {lo, hi};\n"
                 "st.relaxed.gpu.global.b128 [%0], t;\n}"
                 :: "l"(p), "r"(v.x), "r"(v.y), "r"(v.z), "r"(v.w) : "memory");
}
__device__ __forceinline__ void st_mail8(void* p, uint2 v) {
    asm volatile("st.relaxed.gpu.global.b64 [%0], %1;" :: "l"(p), "l"(((unsigned long long)v.y << 32) | v.x) : "memory");
}
__device__ __forceinline__ uint8_t* mail_w(uint8_t* base, uint32_t off) { return base + ((off >> 12) << 13) + (off & 4095u); }
__device__ __forceinline__ uint32_t mail_par(uint32_t off) { const uint32_t j = off >> 12; return (j ^ (j >> 3) ^ (j >> 4) ^ (j >> 6)) & 1u; }
__device__ __forceinline__ const uint8_t* mail_r(uint8_t* base, uint32_t off, uint32_t side) {
    return mail_w(base, off) + ((mail_par(off) ^ side) << 12);
}
__device__ __forceinline__ void st2_mail16(uint8_t* p, uint4 v) { st_mail16(p, v); st_mail16(p + 4096, v); }
__device__ __forceinline__ void st2_mail8(uint8_t* p, uint2 v) { st_mail8(p, v); st_mail8(p + 4096, v); }
__device__ __forceinline__ uint32_t tg(float x, uint32_t t2) { return (__float_as_uint(x) & ~3u) | t2; }
__device__ __forceinline__ float untg(uint32_t u) { return __uint_as_float(u & ~3u); }
__device__ __forceinline__ float asf(uint32_t u) { return __uint_as_float(u); }
__device__ __forceinline__ bool tok(uint32_t w, uint32_t t2) { return (w & 3u) == t2; }
__device__ __forceinline__ void spin_guard(unsigned& s) { if (++s > SPIN_LIMIT) __trap(); }

template <class T, class Load, class Valid>
__device__ __forceinline__ T poll(Load ld, Valid ok) {
    T a = ld();
    unsigned spins = 0;
    while (!__all_sync(0xffffffffu, ok(a))) { spin_guard(spins); a = ld(); }
    return a;
}

template <int N, int MASK> struct Halve {
    static __device__ __forceinline__ void run(float* v, int lane) {
        const bool up = lane & MASK;
#pragma unroll
        for (int i = 0; i < N / 2; i++) {
            float keep = up ? v[i + N / 2] : v[i];
            float send = up ? v[i] : v[i + N / 2];
            v[i] = keep + __shfl_xor_sync(0xffffffffu, send, MASK);
        }
    }
};
__device__ __forceinline__ int bpos(int r) {
    return (r & ~31) + 8 * ((r >> 1) & 3) + 4 * ((r >> 4) & 1) + 2 * ((r >> 3) & 1) + (r & 1);
}

struct Params {
    const __nv_bfloat16 *x, *c;
    __nv_bfloat16* out;
};
struct Maps { CUtensorMap k, v, v2, wo, wg, wu, wd, wm, wq; };

constexpr float LOG2E = 1.4426950408889634f;
constexpr float SCALE = 0.08838834764831845f;

__global__ void __launch_bounds__(NTHR, 1)
fused_kernel(const Params p, const __grid_constant__ Maps tm)
{
    extern __shared__ uint8_t smem_raw[];
    const uint32_t sbase = (smem_u32(smem_raw) + 1023u) & ~1023u;
    uint8_t* smem = smem_raw + (sbase - smem_u32(smem_raw));
    const int tid = threadIdx.x, lane = tid & 31, warp = tid >> 5;
    const int cta = blockIdx.x;
    const int bat = cta >> 6, hkv = (cta >> 3) & 7, split = cta & 7;
    const int j16 = bat * 8 + split;
    const bool is_ffn = cta < NFFN, is_red = cta >= RED0;
    const bool pro_q = cta >= PQ_0, pro_any = cta >= PM2_0;
    const uint32_t bar_full = sbase + SM_BAR, bar_empty = sbase + SM_BAR + 8 * NST;

    uint8_t* const mbase = reinterpret_cast<uint8_t*>((reinterpret_cast<uintptr_t>(g_mailraw) + (2u << 20) - 1) & ~(uintptr_t)((2u << 20) - 1));
    if (warp == 9) {
        if (lane == 0) {
            uint8_t* p0 = mail_w(mbase, ML_PRB + 32 * cta);
            st2_mail16(p0, make_uint4(0, 0, 0, 0)); st2_mail16(p0 + 16, make_uint4(0, 0, 0, 0));
            { const long long c = clock64(); while (clock64() - c < PROBE_WAIT) {} }
            int best0 = 1 << 30, best1 = 1 << 30;
#pragma unroll 1
            for (int i = 0; i < 2 * PROBE_N; i++) {
                const long long t0 = clock64();
                long long t1 = 0;
                uint32_t v;
                asm volatile("atom.relaxed.gpu.global.add.u32 %0, [%1], 1;" : "=r"(v) : "l"(p0 + 4096 * (i & 1)) : "memory");
                if (v != 0xdeadbeefu) t1 = clock64();
                if (i & 1) best1 = min(best1, (int)(t1 - t0)); else best0 = min(best0, (int)(t1 - t0));
            }
            uint32_t side = mail_par(ML_PRB) ^ (best1 < best0 ? 1u : 0u);
            *reinterpret_cast<volatile uint32_t*>(smem + SM_BAR + 120) = side;
        }
        __syncwarp();
        asm volatile("bar.arrive 3, 288;" ::: "memory");
        return;
    }
    if (warp == 8) {
        const bool pro_m1 = cta >= PM1_0 && !pro_q;
        const int row0 = ((bat * HKV + hkv) * SK + split * TILE_KEYS) * 2;
        uint64_t pol = 0;
        if (lane == 0) {
            asm volatile("prefetch.tensormap [%0];" :: "l"(pro_m1 ? &tm.wm : &tm.k) : "memory");
            for (int i = 0; i < NST; i++) { mbar_init(bar_full + 8 * i, 1); mbar_init(bar_empty + 8 * i, 8); }
            asm volatile("fence.mbarrier_init.release.cluster;" ::: "memory");
            asm volatile("fence.proxy.async.shared::cta;" ::: "memory");
            asm volatile("createpolicy.fractional.L2::evict_first.b64 %0, 1.0;" : "=l"(pol));
            if (pro_m1) {
                mbar_expect_tx(bar_full, TILE_BYTES);
                tma2d(sbase + SM_RING, &tm.wm, 64 * (cta - PM1_0), 0, bar_full, pol);
            } else {
                mbar_expect_tx(bar_full + 8 * IDX0, TILE_BYTES);
                tma2d(sbase + SM_RING + IDX0 * TILE_BYTES, &tm.k, 0, row0, bar_full + 8 * IDX0, pol);
            }
        }
        __syncwarp();
        asm volatile("bar.arrive 2, 288;" ::: "memory");
        if (lane == 0) {
            auto issue_kv = [&](int idx) {
                const int st = idx % NST, row = row0 + ((idx - IDX0) >> 1) * (8 * TILE_KEYS * 2);
                const uint32_t dst = sbase + SM_RING + st * TILE_BYTES;
                mbar_expect_tx(bar_full + 8 * st, TILE_BYTES);
                if (idx == NIDX - 1) {
                    tma2d(dst, &tm.v2, 0, row >> 1, bar_full + 8 * st, pol);
                    tma2d(dst + 16384, &tm.v2, 64, row >> 1, bar_full + 8 * st, pol);
                } else {
                    tma2d(dst, (idx & 1) ? &tm.v : &tm.k, 0, row, bar_full + 8 * st, pol);
                }
            };
            auto issue_pw = [&](int i) {
                const CUtensorMap* m = pro_q ? &tm.wq : &tm.wm;
                const int col = pro_q ? 64 * (cta - PQ_0) : (cta >= PM1_0 ? 64 * (cta - PM1_0) : 2 * D + 64 * (cta - PM2_0));
                mbar_expect_tx(bar_full + 8 * i, TILE_BYTES);
                tma2d(sbase + SM_RING + i * TILE_BYTES, m, col, 256 * i, bar_full + 8 * i, pol);
            };
            if (pro_q) {
                mbar_wait(bar_full + 16, 0); issue_pw(0); issue_pw(1);
                mbar_wait(bar_full, 0); issue_kv(3);
                mbar_wait(bar_full + 8, 0);
            } else if (pro_m1) {
                issue_pw(1);
                mbar_wait(bar_full, 0); issue_kv(2);
                mbar_wait(bar_full + 8, 0); issue_kv(3);
            } else if (pro_any) {
                mbar_wait(bar_full + 16, 0); issue_kv(3); issue_pw(0);
                mbar_wait(bar_full + 24, 0); issue_pw(1);
                mbar_wait(bar_full, 0);
            } else {
                mbar_arrive(bar_full); mbar_arrive(bar_full + 8);
                issue_kv(3);
            }
            auto issue_w = [&](int idx) {
                const int st = idx % NST;
                const uint32_t dst = sbase + SM_RING + st * TILE_BYTES, bar = bar_full + 8 * st;
                mbar_wait(bar_empty + 8 * st, ((idx / NST) & 1) ^ 1);
                mbar_expect_tx(bar, TILE_BYTES);
                if (idx == IDX_WO) {
                    const int h = hkv * 4 + (j16 >> 2), cq = j16 & 3;
                    tma2d(dst, &tm.wo, cq * 128, h * 128, bar, pol);
                    tma2d(dst + 16384, &tm.wo, cq * 128 + 64, h * 128, bar, pol);
                } else if (idx == IDX_WG || idx == IDX_WU) {
                    const CUtensorMap* m = idx == IDX_WG ? &tm.wg : &tm.wu;
                    tma2d(dst, m, cta * FC, 0, bar, pol);
                    tma2d(dst + 16384, m, cta * FC, 256, bar, pol);
                } else {
#pragma unroll
                    for (int cb = 0; cb < 8; cb++) tma2d(dst + cb * 4096, &tm.wd, cb * 64, cta * FC, bar, pol);
                }
            };
            int st = IDX0 + 2, ph = 1;
            int landed = IDX0, st2 = IDX0, ph2 = 0;
            unsigned pbase = 0, pval = 0;
            asm volatile("ld.relaxed.gpu.global.u32 %0, [%1];" : "=r"(pbase) : "l"(&g_epoch) : "memory");
            pbase *= (unsigned)(NCTA * (PROG_END - IDX0));
            pval = pbase;
            auto observe = [&]() {
                mbar_wait(bar_full + 8 * st2, ph2);
                if (landed < PROG_END) asm volatile("red.relaxed.gpu.global.add.u32 [%0], 1;" :: "l"(&g_prog[0]) : "memory");
                landed++;
                if (++st2 == NST) { st2 = 0; ph2 ^= 1; }
            };
            for (int idx = IDX0 + 2; idx < NIDX; idx++) {
                if (idx >= NST) mbar_wait(bar_empty + 8 * st, ph);
                const int lag = (int)((pval - pbase) * 4) - (landed - IDX0) * (4 * NCTA);
                const int win = MAXFLY + (lag > PACE_LAG4 * NCTA ? 1 : 0);
                while (idx - landed >= win) observe();
                {
                    unsigned spins = 0;
                    while ((int)((landed - IDX0) * (4 * NCTA) - PACE_LEAD4 * NCTA) > (int)((pval - pbase) * 4)) {
                        asm volatile("ld.relaxed.gpu.global.u32 %0, [%1];" : "=r"(pval) : "l"(&g_prog[0]) : "memory");
                        if (++spins > SPIN_LIMIT) __trap();
                    }
                }
                issue_kv(idx);
                asm volatile("ld.relaxed.gpu.global.u32 %0, [%1];" : "=r"(pval) : "l"(&g_prog[0]) : "memory");
                if (idx == IDX0 + 3) {
                    asm volatile("prefetch.tensormap [%0];" :: "l"(&tm.v2) : "memory");
                    asm volatile("prefetch.tensormap [%0];" :: "l"(&tm.wo) : "memory");
                    asm volatile("prefetch.tensormap [%0];" :: "l"(&tm.wg) : "memory");
                    asm volatile("prefetch.tensormap [%0];" :: "l"(&tm.wu) : "memory");
                    asm volatile("prefetch.tensormap [%0];" :: "l"(&tm.wd) : "memory");
                }
                if (++st == NST) { st = 0; ph ^= 1; }
                if (idx == WO_AT) {
                    while (landed <= IDX_WO - NST) observe();
                    issue_w(IDX_WO);
                }
            }
            while (landed < PROG_END) observe();
            if (is_ffn) {
                while (landed < NIDX) observe();
                issue_w(IDX_WG); issue_w(IDX_WU); issue_w(IDX_WD);
            }
        }
        return;
    }

    TS_START();
    unsigned tag;
    uint32_t xw[2], cw[2];
    asm volatile("ld.relaxed.gpu.global.u32 %0, [%1];" : "=r"(tag) : "l"(&g_epoch) : "memory");
#pragma unroll
    for (int b = 0; b < 2; b++) {
        asm volatile("ld.global.nc.u32 %0, [%1];" : "=r"(cw[b]) : "l"(p.c + b * D + 2 * tid));
        asm volatile("ld.global.nc.u32 %0, [%1];" : "=r"(xw[b]) : "l"(p.x + b * D + 2 * tid));
    }
    const int rr = is_red ? cta - RED0 : tid >> 2, ri = is_red ? (lane & 3) : tid & 3;
    const int colA = 16 * (rr >> 1) + 4 * (rr & 1) + ri, colB = colA + 8;
    uint32_t xr[4];
#pragma unroll
    for (int i = 0; i < 4; i++)
        asm volatile("ld.global.nc.u16 %0, [%1];" : "=r"(xr[i]) : "l"(p.x + (i & 1) * D + ((i >> 1) ? colB : colA)));
    uint2* pout = pro_q ? &g_q[64 * (cta - PQ_0) + (tid & 63)]
                : cta >= PM1_0 ? &g_mod1[(tid >> 6) * 2 * D + 64 * (cta - PM1_0) + (tid & 63)]
                               : &g_mod2[64 * (pro_any ? cta - PM2_0 : 0) + (tid & 63)];
    const bool pwrite = pro_any && (tid < 64 || (cta >= PM1_0 && !pro_q));
    if (pwrite) st_mail8(pout, make_uint2(0, 0));
    const int g = lane >> 2, t = lane & 3;
    float* scr = reinterpret_cast<float*>(smem + SM_SCR);
    uint32_t* bvec = reinterpret_cast<uint32_t*>(smem + SM_SMALL);
    const int bw = bpos(2 * tid) >> 1;
    if (pro_any && !pro_q) {
        float sv[2][2];
#pragma unroll
        for (int b = 0; b < 2; b++) {
            const float c0 = bf_lo(cw[b]), c1 = bf_hi(cw[b]);
            sv[b][0] = __fdividef(c0, 1.f + __expf(-c0)); sv[b][1] = __fdividef(c1, 1.f + __expf(-c1));
        }
        bvec[bw] = pack_bf16(sv[0][0], sv[0][1]); bvec[256 + bw] = pack_bf16(sv[1][0], sv[1][1]);
    }
    tag += 1;
    if (tag == 0) tag = 1;
    const uint32_t t2 = 1 + tag % 3;
    asm volatile("bar.sync 2, 288;" ::: "memory");
    TS(14);
    if (pro_q) {
        float* st = scr + 2048;
        float xv[2][2], s[2], nrm[2][2];
#pragma unroll
        for (int b = 0; b < 2; b++) { xv[b][0] = bf_lo(xw[b]); xv[b][1] = bf_hi(xw[b]); s[b] = xv[b][0] + xv[b][1]; }
#pragma unroll
        for (int o = 16; o; o >>= 1) { s[0] += __shfl_xor_sync(~0u, s[0], o); s[1] += __shfl_xor_sync(~0u, s[1], o); }
        if (lane == 0) { st[warp * 2] = s[0]; st[warp * 2 + 1] = s[1]; }
        cons_bar();
        float mean[2] = {0.f, 0.f};
#pragma unroll
        for (int w = 0; w < 8; w++) { mean[0] += st[w * 2]; mean[1] += st[w * 2 + 1]; }
        mean[0] *= (1.f / D); mean[1] *= (1.f / D);
#pragma unroll
        for (int b = 0; b < 2; b++) {
            float d0 = xv[b][0] - mean[b], d1 = xv[b][1] - mean[b];
            s[b] = d0 * d0 + d1 * d1;
        }
#pragma unroll
        for (int o = 16; o; o >>= 1) { s[0] += __shfl_xor_sync(~0u, s[0], o); s[1] += __shfl_xor_sync(~0u, s[1], o); }
        if (lane == 0) { st[16 + warp * 2] = s[0]; st[16 + warp * 2 + 1] = s[1]; }
        cons_bar();
#pragma unroll
        for (int b = 0; b < 2; b++) {
            float var = 0.f;
#pragma unroll
            for (int w = 0; w < 8; w++) var += st[16 + w * 2 + b];
            const float mb = bfr(mean[b]);
            const float sd = bfr(sqrt_fast(bfr(bfr(var * (1.f / D)) + 1e-5f)));
            nrm[b][0] = bfr(__fdividef(bfr(xv[b][0] - mb), sd));
            nrm[b][1] = bfr(__fdividef(bfr(xv[b][1] - mb), sd));
        }
        unsigned spins = 0;
        const uint2* src = &g_mod1[(cta & (NREPM - 1)) * 2 * D + 2 * tid];
        uint4 sa = ld_mail16(src), ca = ld_mail16(src + D);
        while (sa.y != tag || sa.w != tag || ca.y != tag || ca.w != tag) {
            spin_guard(spins);
            if (sa.y != tag || sa.w != tag) sa = ld_mail16(src);
            if (ca.y != tag || ca.w != tag) ca = ld_mail16(src + D);
        }
        bvec[bw]       = pack_bf16(bfr(nrm[0][0] * bfr(1.f + bf_lo(ca.x))) + bf_lo(sa.x), bfr(nrm[0][1] * bfr(1.f + bf_lo(ca.z))) + bf_lo(sa.z));
        bvec[256 + bw] = pack_bf16(bfr(nrm[1][0] * bfr(1.f + bf_hi(ca.x))) + bf_hi(sa.x), bfr(nrm[1][1] * bfr(1.f + bf_hi(ca.z))) + bf_hi(sa.z));
        cons_bar();
    }
    TS(2);
    if (pro_any) {
        const int slot = warp >> 2;
        mbar_wait(bar_full + 8 * slot, 0);
        TS(15);
        const uint32_t wb = sbase + SM_RING + slot * TILE_BYTES + (warp & 3) * (64 * 128);
        const int mi = lane >> 3, r = lane & 7;
        uint4 bq[2];
#pragma unroll
        for (int kk = 0; kk < 2; kk++)
            bq[kk] = g < 2 ? *reinterpret_cast<const uint4*>(bvec + g * 256 + 32 * warp + 16 * kk + 4 * t) : make_uint4(0, 0, 0, 0);
        float c[4][4];
#pragma unroll
        for (int mt = 0; mt < 4; mt++) {
            c[mt][0] = c[mt][1] = c[mt][2] = c[mt][3] = 0.f;
#pragma unroll
            for (int ks = 0; ks < 4; ks++) {
                uint32_t a[4];
                ldsm4t(a, wb + (16 * ks + 8 * (mi >> 1) + r) * 128 + (((2 * mt + (mi & 1)) ^ r) << 4));
                mma16816(c[mt], a, (ks & 1) ? bq[ks >> 1].z : bq[ks >> 1].x, (ks & 1) ? bq[ks >> 1].w : bq[ks >> 1].y);
            }
        }
        if (t == 0) {
#pragma unroll
            for (int mt = 0; mt < 4; mt++) {
                *reinterpret_cast<float2*>(scr + (warp * 64 + 16 * mt + g) * 2)     = make_float2(c[mt][0], c[mt][1]);
                *reinterpret_cast<float2*>(scr + (warp * 64 + 16 * mt + 8 + g) * 2) = make_float2(c[mt][2], c[mt][3]);
            }
        }
        cons_bar();
        if (pwrite) {
            float2 v[8];
#pragma unroll
            for (int w = 0; w < 8; w++) v[w] = *reinterpret_cast<const float2*>(scr + (w * 64 + (tid & 63)) * 2);
            st_mail8(pout, make_uint2(pack_bf16(((v[0].x + v[1].x) + (v[2].x + v[3].x)) + ((v[4].x + v[5].x) + (v[6].x + v[7].x)),
                                                ((v[0].y + v[1].y) + (v[2].y + v[3].y)) + ((v[4].y + v[5].y) + (v[6].y + v[7].y))), tag));
        }
    }
    __syncwarp();
    if (lane == 0) { mbar_arrive(bar_empty); mbar_arrive(bar_empty + 8); }
    TS(3);
    uint32_t qf[8][2];
    {
        unsigned spins = 0;
        const uint2* src = &g_q[hkv * 512 + 2 * tid];
        uint4 v = ld_mail16(src);
        while (v.y != tag || v.w != tag) { spin_guard(spins); v = ld_mail16(src); }
        uint32_t* qs = reinterpret_cast<uint32_t*>(scr + 2176);
        const uint32_t w = bat ? ((v.x >> 16) | (v.z & 0xffff0000u)) : ((v.x & 0xffffu) | (v.z << 16));
        qs[(tid >> 6) * 68 + (tid & 63)] = w;
        cons_bar();
#pragma unroll
        for (int ks = 0; ks < 8; ks++) {
            qf[ks][0] = g < 4 ? qs[g * 68 + 8 * ks + t] : 0u;
            qf[ks][1] = g < 4 ? qs[g * 68 + 8 * ks + 4 + t] : 0u;
        }
    }
    TS(4);

    uint32_t mA0 = 0, mB0 = 0, mA1 = 0, mB1 = 0;
    uint32_t wa[8][4];
    float oacc[8][4];
#pragma unroll
    for (int i = 0; i < 8; i++) { oacc[i][0] = oacc[i][1] = oacc[i][2] = oacc[i][3] = 0.f; }
    float m0 = -INFINITY, m1 = -INFINITY, l0 = 0.f, l1 = 0.f;
    float* sm_m = reinterpret_cast<float*>(smem + SM_ML);
    float* sm_l = sm_m + 32;
    auto init_mail = [&]() {
        const uint32_t d1 = ML_H1 + 4 * (((hkv * 16 + j16) * 4 + (tid & 3)) * H1_HS);
        st2_mail8(mail_w(mbase, d1 + 8 * (tid >> 2)), make_uint2(0, 0));
        if (tid < 16) st2_mail8(mail_w(mbase, d1 + 512 + 8 * (tid >> 2)), make_uint2(0, 0));
        if (t == 0) {
            const int mt = (j16 & 3) * 8 + warp;
            st2_mail16(mail_w(mbase, ML_RS1 + 16 * (((2 * mt + (g >> 2)) * 32 + hkv * 4 + (j16 >> 2)) * 4 + (g & 3))), make_uint4(0, 0, 0, 0));
            if (is_ffn) {
#pragma unroll
                for (int jm = 0; jm < 4; jm++)
                    st2_mail16(mail_w(mbase, ML_RS3 + 16 * (((2 * (4 * warp + jm) + (g >> 2)) * NFFN + cta) * 4 + (g & 3))), make_uint4(0, 0, 0, 0));
            }
        }
        if (is_red && warp == 0) st_mail16(mail_w(mbase, ML_AG + 4096 * (g >> 1) + 16 * ((cta - RED0) * 4 + t)) + 4096 * (g & 1), make_uint4(0, 0, 0, 0));
    };
    const int keyK = warp * 16 + (lane & 7) + 8 * ((lane >> 3) & 1);
    const uint32_t kA = keyK * 256, kX = (((lane >> 4) ^ (2 * (keyK & 3))) << 4);
    const int keyV = warp * 16 + (lane & 7) + 8 * (lane >> 4);
    const uint32_t vA = keyV * 256, vX = ((((lane >> 3) & 1) ^ (2 * (keyV & 3))) << 4);
    int st = IDX0, ph = 0;
    auto qk_tile = [&](float& c0, float& c1, float& c2, float& c3, float& x0, float& x1) {
        const uint32_t base = sbase + SM_RING + st * TILE_BYTES + kA;
        mbar_wait(bar_full + 8 * st, ph);
        float s0[4] = {0.f, 0.f, 0.f, 0.f}, s1[4] = {0.f, 0.f, 0.f, 0.f};
#pragma unroll
        for (int ks = 0; ks < 8; ks++) {
            uint32_t a[4];
            const int hf = ks >> 2;
            ldsm4(a, base + hf * 128 + ((((2 * (ks & 3)) ^ hf) << 4) ^ kX));
            if (ks & 1) mma16816(s1, a, qf[ks][0], qf[ks][1]); else mma16816(s0, a, qf[ks][0], qf[ks][1]);
        }
        __syncwarp();
        if (lane == 0) mbar_arrive(bar_empty + 8 * st);
        if (++st == NST) { st = 0; ph ^= 1; }
        const uint32_t ra = pack_bf16(s0[0] + s1[0], s0[1] + s1[1]), rb = pack_bf16(s0[2] + s1[2], s0[3] + s1[3]);
        const uint32_t sa = pack_bf16(bf_lo(ra) * SCALE, bf_hi(ra) * SCALE), sb = pack_bf16(bf_lo(rb) * SCALE, bf_hi(rb) * SCALE);
        c0 = bf_lo(sa); c1 = bf_hi(sa); c2 = bf_lo(sb); c3 = bf_hi(sb);
        x0 = fmaxf(c0, c2); x1 = fmaxf(c1, c3);
#pragma unroll
        for (int o = 4; o <= 16; o <<= 1) {
            x0 = fmaxf(x0, __shfl_xor_sync(~0u, x0, o));
            x1 = fmaxf(x1, __shfl_xor_sync(~0u, x1, o));
        }
    };
    auto softmax_tile = [&](float c0, float c1, float c2, float c3, float x0, float x1, uint32_t& b0, uint32_t& b1) {
        if (__any_sync(~0u, x0 > m0 || x1 > m1)) {
            const float n0 = fmaxf(m0, x0), n1 = fmaxf(m1, x1);
            const float f0 = ex2((m0 - n0) * LOG2E), f1 = ex2((m1 - n1) * LOG2E);
            m0 = n0; m1 = n1; l0 *= f0; l1 *= f1;
#pragma unroll
            for (int i = 0; i < 8; i++) { oacc[i][0] *= f0; oacc[i][1] *= f1; oacc[i][2] *= f0; oacc[i][3] *= f1; }
        }
        const float p0 = ex2((c0 - m0) * LOG2E), p1 = ex2((c1 - m1) * LOG2E);
        const float p2 = ex2((c2 - m0) * LOG2E), p3 = ex2((c3 - m1) * LOG2E);
        l0 += p0 + p2; l1 += p1 + p3;
        b0 = movtrans(pack_bf16(p0, p1)); b1 = movtrans(pack_bf16(p2, p3));
    };
    for (int it = 0; it < NTILES - 1; it++) {
        if (it == 2 && (is_ffn || is_red)) {
            const int o0 = is_ffn ? D : 0, o1 = is_ffn ? 2 * D : 3 * D;
            unsigned spins = 0;
            uint2 a0, b0, a1, b1;
            for (;;) {
                a0 = ld_mail8(&g_mod2[o0 + colA]); b0 = ld_mail8(&g_mod2[o0 + colB]);
                a1 = ld_mail8(&g_mod2[o1 + colA]); b1 = ld_mail8(&g_mod2[o1 + colB]);
                if (a0.y == tag && b0.y == tag && a1.y == tag && b1.y == tag) break;
                spin_guard(spins); __nanosleep(40);
            }
            mA0 = a0.x; mB0 = b0.x; mA1 = a1.x; mB1 = b1.x;
            if (is_ffn) {
                mA1 = pack_bf16(1.f + bf_lo(mA1), 1.f + bf_hi(mA1)); mB1 = pack_bf16(1.f + bf_lo(mB1), 1.f + bf_hi(mB1));
                uint16_t* cs = reinterpret_cast<uint16_t*>(smem + SM_CS);
                const int pA = bpos(colA), pB = bpos(colB);
                cs[pA] = (uint16_t)mA1; cs[D + pA] = (uint16_t)(mA1 >> 16); cs[2 * D + pA] = (uint16_t)mA0; cs[3 * D + pA] = (uint16_t)(mA0 >> 16);
                cs[pB] = (uint16_t)mB1; cs[D + pB] = (uint16_t)(mB1 >> 16); cs[2 * D + pB] = (uint16_t)mB0; cs[3 * D + pB] = (uint16_t)(mB0 >> 16);
            }
        }
        if (it == WARM_AT) init_mail();
        float c0, c1, c2, c3, x0, x1;
        uint32_t b0, b1;
        qk_tile(c0, c1, c2, c3, x0, x1);
        softmax_tile(c0, c1, c2, c3, x0, x1, b0, b1);
        const uint32_t base = sbase + SM_RING + st * TILE_BYTES + vA;
        mbar_wait(bar_full + 8 * st, ph);
#pragma unroll
        for (int i = 0; i < 8; i++) {
            uint32_t a[4];
            const int hf = i >> 2;
            ldsm4t(a, base + hf * 128 + ((((2 * (i & 3)) ^ hf) << 4) ^ vX));
            mma16816(oacc[i], a, b0, b1);
        }
        __syncwarp();
        if (lane == 0) mbar_arrive(bar_empty + 8 * st);
        if (++st == NST) { st = 0; ph ^= 1; }
    }
    asm volatile("bar.sync 3, 288;" ::: "memory");
    const uint32_t side = *reinterpret_cast<volatile uint32_t*>(smem + SM_BAR + 120);
    {
        float c0, c1, c2, c3, x0, x1;
        uint32_t b0, b1;
        qk_tile(c0, c1, c2, c3, x0, x1);
        x0 = fmaxf(x0, m0); x1 = fmaxf(x1, m1);
        if (g == 0 && t < 2) { sm_m[warp * 4 + 2 * t] = x0; sm_m[warp * 4 + 2 * t + 1] = x1; }
        cons_bar();
#pragma unroll
        for (int w = 0; w < 8; w++) {
            const float2 mm = *reinterpret_cast<const float2*>(sm_m + w * 4 + 2 * (t & 1));
            x0 = fmaxf(x0, mm.x); x1 = fmaxf(x1, mm.y);
        }
        softmax_tile(c0, c1, c2, c3, x0, x1, b0, b1);
        uint2* sp = reinterpret_cast<uint2*>(smem + SM_SMALL + 2048);
        sp[warp * 32 + lane] = make_uint2(b0, b1);
#pragma unroll
        for (int o = 4; o <= 16; o <<= 1) { l0 += __shfl_xor_sync(~0u, l0, o); l1 += __shfl_xor_sync(~0u, l1, o); }
        if (g == 0 && t < 2) { sm_l[warp * 4 + 2 * t] = l0; sm_l[warp * 4 + 2 * t + 1] = l1; }
        float* ro = scr + warp * 576;
        if (t < 2) {
#pragma unroll
            for (int i = 0; i < 8; i++) {
                const int d = 16 * i + g;
                *reinterpret_cast<float2*>(ro + d * 4 + 2 * t + 4 * (d >> 3))             = make_float2(oacc[i][0], oacc[i][1]);
                *reinterpret_cast<float2*>(ro + (d + 8) * 4 + 2 * t + 4 * ((d + 8) >> 3)) = make_float2(oacc[i][2], oacc[i][3]);
            }
        }
        cons_bar();
        float acc[4][4];
#pragma unroll
        for (int i = 0; i < 4; i++) acc[i][0] = acc[i][1] = acc[i][2] = acc[i][3] = 0.f;
        if (t < 2) {
            const int d = 16 * warp + g;
#pragma unroll
            for (int w = 0; w < 8; w++) {
                const float2 u = *reinterpret_cast<const float2*>(scr + w * 576 + d * 4 + 2 * t + 4 * (d >> 3));
                const float2 v = *reinterpret_cast<const float2*>(scr + w * 576 + (d + 8) * 4 + 2 * t + 4 * ((d + 8) >> 3));
                acc[w & 3][0] += u.x; acc[w & 3][1] += u.y; acc[w & 3][2] += v.x; acc[w & 3][3] += v.y;
            }
        }
        uint2 pb[8];
#pragma unroll
        for (int j = 0; j < 8; j++) pb[j] = sp[j * 32 + lane];
        const uint32_t dst = ML_H1 + 4 * ((hkv * 16 + j16) * 4 * H1_HS);
        if (tid < 16) {
            const int hd = tid & 3;
            float L = 0.f, M = sm_m[hd];
#pragma unroll
            for (int w = 0; w < 8; w++) { L += sm_l[w * 4 + hd]; M = fmaxf(M, sm_m[w * 4 + hd]); }
            st2_mail8(mail_w(mbase, dst + 4 * (hd * H1_HS + 128 + 2 * (tid >> 2))), make_uint2(__float_as_uint(M), tg(L, t2)));
        }
        {
            static_assert(WO_AT >= IDX_WO - NST + 1 && WO_AT < NIDX - 2, "wo must be requested after its slot's last user and before the last K tile");
            mbar_wait(bar_full + 8 * (IDX_WO % NST), (IDX_WO / NST) & 1);
            const uint32_t wb = sbase + SM_RING + (IDX_WO % NST) * TILE_BYTES + (warp >> 2) * 16384;
            const int mi = lane >> 3, r = lane & 7, chunk = 2 * (warp & 3) + (mi & 1);
#pragma unroll
            for (int ks = 0; ks < 8; ks++) ldsm4t(wa[ks], wb + (16 * ks + 8 * (mi >> 1) + r) * 128 + ((chunk ^ r) << 4));
        }
        const uint32_t vb = sbase + SM_RING + st * TILE_BYTES + (warp >> 2) * 16384 + ((lane & 7) + 8 * (lane >> 4)) * 128
                          + (((2 * (warp & 3) + ((lane >> 3) & 1)) ^ (lane & 7)) << 4);
        uint8_t* pub0 = mail_w(mbase, dst + 4 * ((2 * (t & 1)) * H1_HS + 16 * warp + 2 * g));
        uint8_t* pub1 = mail_w(mbase, dst + 4 * ((2 * (t & 1) + 1) * H1_HS + 16 * warp + 2 * g));
        asm volatile("" : "+l"(pub0), "+l"(pub1));
        mbar_wait(bar_full + 8 * st, ph);
        TS(5); TS_CAL();
#pragma unroll
        for (int j = 0; j < 8; j++) {
            uint32_t a[4];
            ldsm4t(a, vb + j * (16 * 128));
            mma16816(acc[j & 3], a, pb[j].x, pb[j].y);
        }
        if (t < 2) {
            const float r0 = (acc[0][0] + acc[1][0]) + (acc[2][0] + acc[3][0]), r1 = (acc[0][1] + acc[1][1]) + (acc[2][1] + acc[3][1]);
            const float r2 = (acc[0][2] + acc[1][2]) + (acc[2][2] + acc[3][2]), r3 = (acc[0][3] + acc[1][3]) + (acc[2][3] + acc[3][3]);
            st2_mail8(pub0, make_uint2(__float_as_uint(r0), tg(r2, t2)));
            st2_mail8(pub1, make_uint2(__float_as_uint(r1), tg(r3, t2)));
        }
    }
    TS(6);
    uint32_t* os = reinterpret_cast<uint32_t*>(smem + SM_SMALL);
    {
        uint8_t* rs1dst = mail_w(mbase, ML_RS1 + 16 * (((2 * ((j16 & 3) * 8 + warp) + (g >> 2)) * 32 + hkv * 4 + (j16 >> 2)) * 4 + (g & 3)));
        asm volatile("" : "+l"(rs1dst));
        float* so = reinterpret_cast<float*>(smem + SM_RING + ((NIDX - 2) % NST) * TILE_BYTES);
        float2* sml = reinterpret_cast<float2*>(so + 2048);
        uint32_t a_ml = smem_u32(sml) + (tid >> 7) * 64, a_ov = smem_u32(so) + (tid >> 7) * 4096 + (tid & 127) * 4;
        uint32_t a_os = smem_u32(os) + 2 * ((tid >> 7) * 128 + bpos(((tid & 127) & ~15) + ((tid & 15) >> 1) + 8 * (tid & 1)));
        uint32_t a_bq = smem_u32(os) + (g & 1) * 256 + 16 * t;
        uint4 bq[4] = {make_uint4(0, 0, 0, 0), make_uint4(0, 0, 0, 0), make_uint4(0, 0, 0, 0), make_uint4(0, 0, 0, 0)};
        pin(a_ml); pin(a_ov); pin(a_os); pin(a_bq); pin4(bq[0]); pin4(bq[1]); pin4(bq[2]); pin4(bq[3]);
        {
            const uint32_t off0 = ML_H1 + 4 * (((hkv * 16 + warp) * 4 + (j16 >> 2)) * H1_HS), off1 = off0 + 4 * (8 * 4 * H1_HS);
            const uint8_t* po0 = mail_r(mbase, off0 + 16 * lane, side);
            const uint8_t* po1 = mail_r(mbase, off1 + 16 * lane, side);
            const uint8_t* pm0 = mail_r(mbase, off0 + 512, side);
            const uint8_t* pm1 = mail_r(mbase, off1 + 512, side);
            struct H1Msg { uint4 o0, o1; uint2 m0, m1; };
            const H1Msg v = poll<H1Msg>(
                [&] { H1Msg r; r.o0 = ld_mail16(po0); r.o1 = ld_mail16(po1); r.m0 = ld_mail8(pm0); r.m1 = ld_mail8(pm1); return r; },
                [&](const H1Msg& r) { return ((((r.o0.y ^ t2) | (r.o0.w ^ t2)) | ((r.o1.y ^ t2) | (r.o1.w ^ t2)) | (r.m0.y ^ t2) | (r.m1.y ^ t2)) & 3u) == 0; });
            *reinterpret_cast<float4*>(so + warp * 128 + 4 * lane)        = make_float4(asf(v.o0.x), untg(v.o0.y), asf(v.o0.z), untg(v.o0.w));
            *reinterpret_cast<float4*>(so + 1024 + warp * 128 + 4 * lane) = make_float4(asf(v.o1.x), untg(v.o1.y), asf(v.o1.z), untg(v.o1.w));
            if (lane == 0) { sml[warp] = make_float2(asf(v.m0.x), untg(v.m0.y)); sml[8 + warp] = make_float2(asf(v.m1.x), untg(v.m1.y)); }
        }
        cons_bar();
        TSB(7);
        {
            float2 ml[8];
            float ov[8];
            ml[0] = lds64<0>(a_ml); ml[1] = lds64<8>(a_ml); ml[2] = lds64<16>(a_ml); ml[3] = lds64<24>(a_ml);
            ml[4] = lds64<32>(a_ml); ml[5] = lds64<40>(a_ml); ml[6] = lds64<48>(a_ml); ml[7] = lds64<56>(a_ml);
            ov[0] = lds32<0>(a_ov); ov[1] = lds32<512>(a_ov); ov[2] = lds32<1024>(a_ov); ov[3] = lds32<1536>(a_ov);
            ov[4] = lds32<2048>(a_ov); ov[5] = lds32<2560>(a_ov); ov[6] = lds32<3072>(a_ov); ov[7] = lds32<3584>(a_ov);
            const float M = fmaxf(fmaxf(fmaxf(ml[0].x, ml[1].x), fmaxf(ml[2].x, ml[3].x)), fmaxf(fmaxf(ml[4].x, ml[5].x), fmaxf(ml[6].x, ml[7].x)));
            float L0 = 0.f, L1 = 0.f, o0 = 0.f, o1 = 0.f;
#pragma unroll
            for (int s = 0; s < 8; s += 2) {
                const float f0 = ex2((ml[s].x - M) * LOG2E), f1 = ex2((ml[s + 1].x - M) * LOG2E);
                L0 += f0 * ml[s].y; L1 += f1 * ml[s + 1].y; o0 += f0 * ov[s]; o1 += f1 * ov[s + 1];
            }
            float rl;
            asm("rcp.approx.ftz.f32 %0, %1;" : "=f"(rl) : "f"(L0 + L1));
            sts16<0>(a_os, pack_bf16((o0 + o1) * rl, 0.f));
        }
        cons_bar();
        TSB(8);
        float c0[4] = {0.f, 0.f, 0.f, 0.f}, c1[4] = {0.f, 0.f, 0.f, 0.f}, c2[4] = {0.f, 0.f, 0.f, 0.f}, c3[4] = {0.f, 0.f, 0.f, 0.f};
        lds128_if<0>(bq[0], a_bq, g < 2); lds128_if<64>(bq[1], a_bq, g < 2); lds128_if<128>(bq[2], a_bq, g < 2); lds128_if<192>(bq[3], a_bq, g < 2);
        mma16816(c0, wa[0], bq[0].x, bq[0].y); mma16816(c1, wa[1], bq[0].z, bq[0].w);
        mma16816(c2, wa[2], bq[1].x, bq[1].y); mma16816(c3, wa[3], bq[1].z, bq[1].w);
        mma16816(c0, wa[4], bq[2].x, bq[2].y); mma16816(c1, wa[5], bq[2].z, bq[2].w);
        mma16816(c2, wa[6], bq[3].x, bq[3].y); mma16816(c3, wa[7], bq[3].z, bq[3].w);
        if (t == 0) {
            st2_mail16(rs1dst,
                      make_uint4(__float_as_uint((c0[0] + c1[0]) + (c2[0] + c3[0])), __float_as_uint((c0[1] + c1[1]) + (c2[1] + c3[1])),
                                 __float_as_uint((c0[2] + c1[2]) + (c2[2] + c3[2])), tg((c0[3] + c1[3]) + (c2[3] + c3[3]), t2)));
        }
    }
    TS(9);

    if (is_red) {
        if (warp == 0) {
            const int r = cta - RED0, ps = g;
            const float xA0 = bf_lo(xr[0]), xA1 = bf_lo(xr[1]), xB0 = bf_lo(xr[2]), xB1 = bf_lo(xr[3]);
            uint4 v[4];
            const uint4* src = reinterpret_cast<const uint4*>(mail_r(mbase, ML_RS1 + 16 * ((r * 32 + ps) * 4 + ri), side));
            uint8_t* agdst = mail_w(mbase, ML_AG + 4096 * (ps >> 1) + 16 * (r * 4 + ri)) + 4096 * (ps & 1);
            const uint4* src3[7];
#pragma unroll
            for (int j = 0; j < 7; j++) src3[j] = reinterpret_cast<const uint4*>(mail_r(mbase, ML_RS3 + 16 * ((r * NFFN + ps + 8 * j) * 4 + ri), side));
#pragma unroll
            for (int j = 0; j < 4; j++) v[j] = ld_mail16(src + j * 32);
            unsigned spins = 0;
            while (!__all_sync(~0u, (((v[0].w ^ t2) | (v[1].w ^ t2) | (v[2].w ^ t2) | (v[3].w ^ t2)) & 3u) == 0)) {
                spin_guard(spins);
#pragma unroll
                for (int j = 0; j < 4; j++) if (!tok(v[j].w, t2)) v[j] = ld_mail16(src + j * 32);
            }
            __syncwarp();
            float s[4];
            s[0] = (asf(v[0].x) + asf(v[1].x)) + (asf(v[2].x) + asf(v[3].x));
            s[1] = (asf(v[0].y) + asf(v[1].y)) + (asf(v[2].y) + asf(v[3].y));
            s[2] = (asf(v[0].z) + asf(v[1].z)) + (asf(v[2].z) + asf(v[3].z));
            s[3] = (untg(v[0].w) + untg(v[1].w)) + (untg(v[2].w) + untg(v[3].w));
#pragma unroll
            for (int o = 4; o <= 16; o <<= 1)
#pragma unroll
                for (int k = 0; k < 4; k++) s[k] += __shfl_xor_sync(~0u, s[k], o);
            const float yA0 = bfr(xA0 + bfr(bf_lo(mA0) * bfr(s[0]))), yA1 = bfr(xA1 + bfr(bf_hi(mA0) * bfr(s[1])));
            const float yB0 = bfr(xB0 + bfr(bf_lo(mB0) * bfr(s[2]))), yB1 = bfr(xB1 + bfr(bf_hi(mB0) * bfr(s[3])));
            st_mail16(agdst,
                      make_uint4(__float_as_uint(yA0), __float_as_uint(yA1), __float_as_uint(yB0), __float_as_uint(yB1) | t2));
            TS(10);
            uint4 f[7];
#pragma unroll
            for (int j = 0; j < 7; j++) f[j] = ld_mail16(src3[j]);
            for (;;) {
                uint32_t bad = 0;
#pragma unroll
                for (int j = 0; j < 7; j++) bad |= f[j].w ^ t2;
                if (__all_sync(~0u, (bad & 3u) == 0)) break;
                spin_guard(spins);
#pragma unroll
                for (int j = 0; j < 7; j++) if (!tok(f[j].w, t2)) f[j] = ld_mail16(src3[j]);
            }
            __syncwarp();
            s[0] = ((asf(f[0].x) + asf(f[1].x)) + (asf(f[2].x) + asf(f[3].x))) + ((asf(f[4].x) + asf(f[5].x)) + asf(f[6].x));
            s[1] = ((asf(f[0].y) + asf(f[1].y)) + (asf(f[2].y) + asf(f[3].y))) + ((asf(f[4].y) + asf(f[5].y)) + asf(f[6].y));
            s[2] = ((asf(f[0].z) + asf(f[1].z)) + (asf(f[2].z) + asf(f[3].z))) + ((asf(f[4].z) + asf(f[5].z)) + asf(f[6].z));
            s[3] = ((untg(f[0].w) + untg(f[1].w)) + (untg(f[2].w) + untg(f[3].w))) + ((untg(f[4].w) + untg(f[5].w)) + untg(f[6].w));
#pragma unroll
            for (int o = 4; o <= 16; o <<= 1)
#pragma unroll
                for (int k = 0; k < 4; k++) s[k] += __shfl_xor_sync(~0u, s[k], o);
            if (ps == 0) {
                p.out[colA]     = __float2bfloat16(yA0 + bfr(bf_lo(mA1) * bfr(s[0])));
                p.out[D + colA] = __float2bfloat16(yA1 + bfr(bf_hi(mA1) * bfr(s[1])));
                p.out[colB]     = __float2bfloat16(yB0 + bfr(bf_lo(mB1) * bfr(s[2])));
                p.out[D + colB] = __float2bfloat16(yB1 + bfr(bf_hi(mB1) * bfr(s[3])));
            }
            TS(11);
            if (cta == RED0 && tid == 0)
                asm volatile("st.relaxed.gpu.global.u32 [%0], %1;" :: "l"(&g_epoch), "r"(tag) : "memory");
        }
    } else if (is_ffn) {
        const int mat = warp >> 2, kq = warp & 3;
        uint32_t ga[2][8][4], da[4][2][4];
        {
            const int idx = IDX_WG + mat;
            mbar_wait(bar_full + 8 * (idx % NST), (idx / NST) & 1);
            const uint32_t wb = sbase + SM_RING + (idx % NST) * TILE_BYTES;
            const int mi = lane >> 3, r = lane & 7;
#pragma unroll
            for (int ks = 0; ks < 8; ks++) {
                const int row = 128 * kq + 16 * ks + 8 * (mi >> 1) + r;
#pragma unroll
                for (int mt = 0; mt < 2; mt++) {
                    const int chunk = 2 * mt + (mi & 1);
                    ldsm4t(ga[mt][ks], wb + row * 64 + ((chunk ^ ((r >> 1) & 3)) << 4));
                }
            }
            mbar_wait(bar_full + 8 * (IDX_WD % NST), (IDX_WD / NST) & 1);
            const uint32_t db = sbase + SM_RING + (IDX_WD % NST) * TILE_BYTES + warp * 4096;
#pragma unroll
            for (int u = 0; u < 2; u++) {
                const int row = 16 * u + 8 * (mi >> 1) + r;
#pragma unroll
                for (int jm = 0; jm < 4; jm++) {
                    const int chunk = 2 * jm + (mi & 1);
                    ldsm4t(da[jm][u], db + row * 128 + ((chunk ^ r) << 4));
                }
            }
        }
        float* red = scr;
        float* red2 = scr + 1024;
        float gA = 0.f, gB = 0.f, uA = 0.f, uB = 0.f;
        const int ef = tid >> 1, eb = tid & 1;
        {
            const uint32_t* csw = reinterpret_cast<const uint32_t*>(smem + SM_CS);
            float c[2][2][4];
#pragma unroll
            for (int mt = 0; mt < 2; mt++)
#pragma unroll
                for (int u = 0; u < 2; u++) c[mt][u][0] = c[mt][u][1] = c[mt][u][2] = c[mt][u][3] = 0.f;
#pragma unroll
            for (int kk = 0; kk < 4; kk++) {
                const uint4 bq = g < 4 ? *reinterpret_cast<const uint4*>(csw + g * 256 + 64 * kq + 16 * kk + 4 * t) : make_uint4(0, 0, 0, 0);
#pragma unroll
                for (int mt = 0; mt < 2; mt++) {
                    mma16816(c[mt][0], ga[mt][2 * kk], bq.x, bq.y);
                    mma16816(c[mt][1], ga[mt][2 * kk + 1], bq.z, bq.w);
                }
            }
            if (t < 2) {
#pragma unroll
                for (int mt = 0; mt < 2; mt++) {
                    *reinterpret_cast<float2*>(red2 + (warp * 32 + mt * 16 + g) * 4 + 2 * t)     = make_float2(c[mt][0][0] + c[mt][1][0], c[mt][0][1] + c[mt][1][1]);
                    *reinterpret_cast<float2*>(red2 + (warp * 32 + mt * 16 + 8 + g) * 4 + 2 * t) = make_float2(c[mt][0][2] + c[mt][1][2], c[mt][0][3] + c[mt][1][3]);
                }
            }
            cons_bar();
            if (tid < 64) {
#pragma unroll
                for (int k = 0; k < 4; k++) {
                    gA += red2[(k * 32 + ef) * 4 + eb];       gB += red2[(k * 32 + ef) * 4 + 2 + eb];
                    uA += red2[((4 + k) * 32 + ef) * 4 + eb]; uB += red2[((4 + k) * 32 + ef) * 4 + 2 + eb];
                }
            }
        }
        TS(10);
        {
            const uint8_t* srcs = mail_r(mbase, ML_AG + 4096 * (cta & (NREP / 2 - 1)), side);
            const uint8_t* src0 = srcs + 16 * tid;
            uint8_t* rs3d[4];
#pragma unroll
            for (int jm = 0; jm < 4; jm++) {
                rs3d[jm] = mail_w(mbase, ML_RS3 + 16 * (((2 * (4 * warp + jm) + (g >> 2)) * NFFN + cta) * 4 + (g & 3)));
                asm volatile("" : "+l"(rs3d[jm]));
            }
            const uint32_t small = sbase + SM_SMALL;
            static_assert(SM_CS == SM_SMALL + 4096, "layout");
            uint32_t a_yA = small + 2 * bpos(colA), a_yB = small + 2 * bpos(colB);
            uint32_t a_by = small + (g & 1) * 1024 + 256 * kq + 16 * t, a_bx = a_by + 4096 + 128 * mat;
            uint32_t a_red = smem_u32(red) + (warp * 32 + g) * 8, a_stt = small + 2048 + warp * 16 + (g == 2 ? 8 : 4 * (g & 1));
            uint32_t a_ep = smem_u32(red) + ef * 8 + eb * 4, a_es = small + 2048 + eb * 4, a_as = small + 3072 + 2 * (eb * 32 + bpos(ef & 31));
            uint32_t a_ab = small + 3072 + (g & 1) * 64 + 16 * t;
            uint4 bq[4] = {make_uint4(0, 0, 0, 0), make_uint4(0, 0, 0, 0), make_uint4(0, 0, 0, 0), make_uint4(0, 0, 0, 0)};
            uint4 bx[2] = {make_uint4(0, 0, 0, 0), make_uint4(0, 0, 0, 0)}, ab = make_uint4(0, 0, 0, 0);
            uint32_t one = g == 2 ? 0x3F803F80u : 0u, gl2 = g < 2;
            pin(a_yA); pin(a_yB); pin(a_by); pin(a_bx); pin(a_red); pin(a_stt); pin(a_ep); pin(a_es); pin(a_as); pin(a_ab); pin(one); pin(gl2);
            pin4(bq[0]); pin4(bq[1]); pin4(bq[2]); pin4(bq[3]); pin4(bx[0]); pin4(bx[1]); pin4(ab);
            struct AgMsg { uint4 v, s; };
            const AgMsg am = poll<AgMsg>([&] { AgMsg r; r.v = ld_mail16(src0); r.s = ld_mail16(srcs); return r; },
                                         [&](const AgMsg& r) { return (((r.v.w ^ t2) | (r.s.w ^ t2)) & 3u) == 0; });
            TS(11);
            const uint4 v = am.v;
            const float sh0 = asf(am.s.x), sh1 = asf(am.s.y);
            const uint32_t yA = pack_bf16((asf(v.x) - sh0) * bf_lo(mA1), (asf(v.y) - sh1) * bf_hi(mA1));
            const uint32_t yB = pack_bf16((asf(v.z) - sh0) * bf_lo(mB1), (untg(v.w) - sh1) * bf_hi(mB1));
            sts16<0>(a_yA, yA); sts16<1024>(a_yA, yA >> 16); sts16<0>(a_yB, yB); sts16<1024>(a_yB, yB >> 16);
            sts16<4096>(a_yA, v.x >> 16); sts16<5120>(a_yA, v.y >> 16); sts16<4096>(a_yB, v.z >> 16); sts16<5120>(a_yB, v.w >> 16);
            cons_bar();
            TSB(12);
            lds128_if<0>(bq[0], a_by, gl2); lds128_if<64>(bq[1], a_by, gl2); lds128_if<128>(bq[2], a_by, gl2); lds128_if<192>(bq[3], a_by, gl2);
            lds128_if<0>(bx[0], a_bx, gl2); lds128_if<64>(bx[1], a_bx, gl2);
            float c[2][4][4];
#pragma unroll
            for (int mt = 0; mt < 2; mt++)
#pragma unroll
                for (int u = 0; u < 4; u++) c[mt][u][0] = c[mt][u][1] = c[mt][u][2] = c[mt][u][3] = 0.f;
#pragma unroll
            for (int kk = 0; kk < 4; kk++)
#pragma unroll
                for (int mt = 0; mt < 2; mt++) {
                    mma16816(c[mt][2 * (kk & 1)], ga[mt][2 * kk], bq[kk].x, bq[kk].y);
                    mma16816(c[mt][2 * (kk & 1) + 1], ga[mt][2 * kk + 1], bq[kk].z, bq[kk].w);
                }
            float z[4][4];
#pragma unroll
            for (int kk = 0; kk < 2; kk++) {
                z[2 * kk][0] = z[2 * kk][1] = z[2 * kk][2] = z[2 * kk][3] = 0.f;
                z[2 * kk + 1][0] = z[2 * kk + 1][1] = z[2 * kk + 1][2] = z[2 * kk + 1][3] = 0.f;
                const uint32_t a0[4] = {bx[kk].x | one, 0u, bx[kk].y | one, 0u}, a1[4] = {bx[kk].z | one, 0u, bx[kk].w | one, 0u};
                mma16816(z[2 * kk], a0, bx[kk].x, bx[kk].y);
                mma16816(z[2 * kk + 1], a1, bx[kk].z, bx[kk].w);
            }
            if (t == 0) {
                sts64<0>(a_red,         (c[0][0][0] + c[0][1][0]) + (c[0][2][0] + c[0][3][0]), (c[0][0][1] + c[0][1][1]) + (c[0][2][1] + c[0][3][1]));
                sts64<64>(a_red,        (c[0][0][2] + c[0][1][2]) + (c[0][2][2] + c[0][3][2]), (c[0][0][3] + c[0][1][3]) + (c[0][2][3] + c[0][3][3]));
                sts64<128>(a_red,       (c[1][0][0] + c[1][1][0]) + (c[1][2][0] + c[1][3][0]), (c[1][0][1] + c[1][1][1]) + (c[1][2][1] + c[1][3][1]));
                sts64<192>(a_red,       (c[1][0][2] + c[1][1][2]) + (c[1][2][2] + c[1][3][2]), (c[1][0][3] + c[1][1][3]) + (c[1][2][3] + c[1][3][3]));
                const float z0 = (z[0][0] + z[1][0]) + (z[2][0] + z[3][0]), z1 = (z[0][1] + z[1][1]) + (z[2][1] + z[3][1]);
                if (g == 2) sts64<0>(a_stt, z0, z1);
                else if (g < 2) sts32<0>(a_stt, g ? z1 : z0);
            }
            cons_bar();
            TSB(19);
            if (tid < 64) {
                const float g0 = lds32<0>(a_ep), g1 = lds32<256>(a_ep), g2 = lds32<512>(a_ep), g3 = lds32<768>(a_ep);
                const float u0 = lds32<1024>(a_ep), u1 = lds32<1280>(a_ep), u2 = lds32<1536>(a_ep), u3 = lds32<1792>(a_ep);
                const float q10 = lds32<8>(a_es), q11 = lds32<24>(a_es), q12 = lds32<40>(a_es), q13 = lds32<56>(a_es);
                const float q14 = lds32<72>(a_es), q15 = lds32<88>(a_es), q16 = lds32<104>(a_es), q17 = lds32<120>(a_es);
                const float q20 = lds32<0>(a_es), q21 = lds32<16>(a_es), q22 = lds32<32>(a_es), q23 = lds32<48>(a_es);
                const float q24 = lds32<64>(a_es), q25 = lds32<80>(a_es), q26 = lds32<96>(a_es), q27 = lds32<112>(a_es);
                const float mean = (((q10 + q11) + (q12 + q13)) + ((q14 + q15) + (q16 + q17))) * (1.f / D);
                const float ex2m = (((q20 + q21) + (q22 + q23)) + ((q24 + q25) + (q26 + q27))) * (1.f / D);
                float rstd;
                asm("rsqrt.approx.ftz.f32 %0, %1;" : "=f"(rstd) : "f"(fmaxf(ex2m - mean * mean, 0.f) + 1e-5f));
                const float dm = bfr(mean) - (eb ? sh1 : sh0);
                const float gs = bfr(rstd * (((g0 + g1) + (g2 + g3)) - dm * gA) + gB);
                const float us = bfr(rstd * (((u0 + u1) + (u2 + u3)) - dm * uA) + uB);
                const float y2 = (-2.f * 0.7978845608028654f * LOG2E) * (gs + 0.044715f * gs * gs * gs);
                float rc;
                asm("rcp.approx.ftz.f32 %0, %1;" : "=f"(rc) : "f"(1.f + ex2(y2)));
                sts16<0>(a_as, pack_bf16(bfr(gs * rc) * us, 0.f));
            }
            cons_bar();
            TSB(20);
            lds128_if<0>(ab, a_ab, gl2);
            float e0[4][4], e1[4][4];
#pragma unroll
            for (int jm = 0; jm < 4; jm++) {
                e0[jm][0] = e0[jm][1] = e0[jm][2] = e0[jm][3] = 0.f;
                e1[jm][0] = e1[jm][1] = e1[jm][2] = e1[jm][3] = 0.f;
                mma16816(e0[jm], da[jm][0], ab.x, ab.y);
                mma16816(e1[jm], da[jm][1], ab.z, ab.w);
            }
            if (t == 0) {
#pragma unroll
                for (int jm = 0; jm < 4; jm++) {
                    st2_mail16(rs3d[jm],
                              make_uint4(__float_as_uint(e0[jm][0] + e1[jm][0]), __float_as_uint(e0[jm][1] + e1[jm][1]),
                                         __float_as_uint(e0[jm][2] + e1[jm][2]), tg(e0[jm][3] + e1[jm][3], t2)));
                }
            }
        }
        TS(13);
    }
    TS_DUMP();
}

typedef CUresult (*EncodeTiledFn)(CUtensorMap*, CUtensorMapDataType, cuuint32_t, void*, const cuuint64_t*, const cuuint64_t*,
                                  const cuuint32_t*, const cuuint32_t*, CUtensorMapInterleave, CUtensorMapSwizzle,
                                  CUtensorMapL2promotion, CUtensorMapFloatOOBfill);

CUtensorMap make_map(EncodeTiledFn enc, const void* ptr, uint64_t inner, uint64_t rows, uint64_t pitch_bytes,
                     uint32_t box_inner, uint32_t box_rows, CUtensorMapSwizzle sw, CUtensorMapL2promotion prom) {
    CUtensorMap m;
    cuuint64_t gd[2] = {inner, rows};
    cuuint64_t gs[1] = {pitch_bytes};
    cuuint32_t bd[2] = {box_inner, box_rows};
    cuuint32_t es[2] = {1, 1};
    enc(&m, CU_TENSOR_MAP_DATA_TYPE_BFLOAT16, 2, const_cast<void*>(ptr), gd, gs, bd, es,
        CU_TENSOR_MAP_INTERLEAVE_NONE, sw, prom, CU_TENSOR_MAP_FLOAT_OOB_FILL_NONE);
    return m;
}

}

extern "C" void kernel_launch(void* const* d_in, const int* in_sizes, int n_in, void* d_out, int out_size) {
    (void)in_sizes; (void)n_in; (void)out_size;
    EncodeTiledFn enc = nullptr;
    cudaDriverEntryPointQueryResult qr;
    cudaGetDriverEntryPoint("cuTensorMapEncodeTiled", reinterpret_cast<void**>(&enc), cudaEnableDefault, &qr);
    const uint64_t kv_rows = (uint64_t)2 * HKV * SK * 2;
    Maps tm;
    tm.k  = make_map(enc, d_in[1], 64, kv_rows, 128, 64, 256, CU_TENSOR_MAP_SWIZZLE_128B, CU_TENSOR_MAP_L2_PROMOTION_NONE);
    tm.v  = make_map(enc, d_in[2], 64, kv_rows, 128, 64, 256, CU_TENSOR_MAP_SWIZZLE_128B, CU_TENSOR_MAP_L2_PROMOTION_NONE);
    tm.v2 = make_map(enc, d_in[2], DH, kv_rows / 2, DH * 2, 64, TILE_KEYS, CU_TENSOR_MAP_SWIZZLE_128B, CU_TENSOR_MAP_L2_PROMOTION_L2_256B);
    tm.wo = make_map(enc, d_in[4], D, HQ * DH, D * 2, 64, 128, CU_TENSOR_MAP_SWIZZLE_128B, CU_TENSOR_MAP_L2_PROMOTION_L2_256B);
    tm.wg = make_map(enc, d_in[6], FF, D, FF * 2, FC, 256, CU_TENSOR_MAP_SWIZZLE_64B, CU_TENSOR_MAP_L2_PROMOTION_L2_128B);
    tm.wu = make_map(enc, d_in[7], FF, D, FF * 2, FC, 256, CU_TENSOR_MAP_SWIZZLE_64B, CU_TENSOR_MAP_L2_PROMOTION_L2_128B);
    tm.wd = make_map(enc, d_in[8], D, FF, D * 2, 64, FC, CU_TENSOR_MAP_SWIZZLE_128B, CU_TENSOR_MAP_L2_PROMOTION_L2_256B);
    tm.wm = make_map(enc, d_in[10], 6 * D, D, 6 * D * 2, 64, 256, CU_TENSOR_MAP_SWIZZLE_128B, CU_TENSOR_MAP_L2_PROMOTION_NONE);
    tm.wq = make_map(enc, d_in[3], HQ * DH, D, HQ * DH * 2, 64, 256, CU_TENSOR_MAP_SWIZZLE_128B, CU_TENSOR_MAP_L2_PROMOTION_NONE);
    Params p;
    p.x = (const __nv_bfloat16*)d_in[0];
    p.c = (const __nv_bfloat16*)d_in[9];
    p.out = (__nv_bfloat16*)d_out;
    cudaFuncSetAttribute(fused_kernel, cudaFuncAttributeMaxDynamicSharedMemorySize, SM_ALLOC);
    fused_kernel<<<NCTA, NTHR, SM_ALLOC>>>(p, tm);
}
```
